```python
import torch

def _softmax(x, axis=-1):
    return torch.softmax(x, dim=axis)
def _gelu(x):
    return torch.nn.functional.gelu(x, approximate="tanh")
def _silu(x):
    return torch.nn.functional.silu(x)
def _sigmoid(x):
    return torch.sigmoid(x)
def _layernorm(x, axis=-1, eps=1e-5):
    m = x.mean(dim=axis, keepdim=True)
    v = x.var(dim=axis, keepdim=True, unbiased=False)
    return (x - m) / torch.sqrt(v + eps)
def _scatter_add(tgt, idx, src, axis=0):
    return tgt.clone().index_add_(axis, idx, src)
def _segment_sum(src, seg, n):
    out = torch.zeros((n,) + src.shape[1:], dtype=src.dtype)
    return out.index_add_(0, seg, src)
def _pad(x, pw):
    flat = tuple(v for pair in reversed(pw) for v in pair)
    return torch.nn.functional.pad(x, flat)

kernel_name = 'gated_mix__sliding_block_cached__glu_gated_geglu__decode'

def setup_inputs():

    _w = (lambda a: (lambda t: t.to(torch.bfloat16) if t.is_floating_point() else t)(torch.as_tensor(a)))
    def _A_setup():
        B, Sq, D = 1, 1, 640
        Hq, Hkv, Sk, Dh = 32, 32, 4096, 192
        assert Hq % Hkv == 0, (Hq, Hkv)
        return {
            "x": _w((lambda *s: torch.randn(*s, dtype=torch.bfloat16) * 0.05)(B, Sq, D)),
            "k_cache": _w((lambda *s: torch.randn(*s, dtype=torch.bfloat16) * 6.4)(B, Hkv, Sk, Dh)),
            "v_cache": _w((lambda *s: torch.randn(*s, dtype=torch.bfloat16) * 0.05)(B, Hkv, Sk, Dh)),
            "wq": _w((lambda *s: torch.randn(*s, dtype=torch.bfloat16) * 6.4)(D, Hq * Dh) * (D ** -0.5)),
            "wo": _w((lambda *s: torch.randn(*s, dtype=torch.bfloat16) * 0.05)(Hq * Dh, D) * ((Hq * Dh) ** -0.5)),
        }
    _A_in = _A_setup()

    def _B_setup():
        B, S, Dm, Df = 1, 1, 640, 1536
        return {
            "x": _w((lambda *s: torch.randn(*s, dtype=torch.bfloat16) * 0.05)(B, S, Dm)),
            "w_gate": _w((lambda *s: torch.randn(*s, dtype=torch.bfloat16) * 0.8)(Dm, Df) * (Dm ** -0.5)),
            "w_up": _w((lambda *s: torch.randn(*s, dtype=torch.bfloat16) * 0.8)(Dm, Df) * (Dm ** -0.5)),
            "w_down": _w((lambda *s: torch.randn(*s, dtype=torch.bfloat16) * 0.8)(Df, Dm) * (Df ** -0.5)),
        }
    _B_in = _B_setup()

    return {
        "A_x": _A_in["x"],
        "A_k_cache": _A_in["k_cache"],
        "A_v_cache": _A_in["v_cache"],
        "A_wq": _A_in["wq"],
        "A_wo": _A_in["wo"],
        "B_x": _B_in["x"],
        "B_w_gate": _B_in["w_gate"],
        "B_w_up": _B_in["w_up"],
        "B_w_down": _B_in["w_down"],
        "gate_w": _w((lambda *s: torch.randn(*s, dtype=torch.bfloat16) * 0.05)(640) * 16.0),
    }

def reference(A_x, A_k_cache, A_v_cache, A_wq, A_wo, B_x, B_w_gate, B_w_up, B_w_down, gate_w):
    def _A_ref(x, k_cache, v_cache, wq, wo):
        B, Sq, D = x.shape
        Hq, Dh = 32, 192
        Hkv, Sk = k_cache.shape[1], k_cache.shape[2]
        W = min(4096, max(256, Sk // 4))
        rep = Hq // Hkv
        q = (lambda x, *d: x.permute(*d))((x @ wq).reshape(B, Sq, Hq, Dh), 0, 2, 1, 3)
        k = (lambda x, n, axis: torch.repeat_interleave(x, n, dim=axis))(k_cache[:, :, Sk - W:, :], rep, axis=1)
        v = (lambda x, n, axis: torch.repeat_interleave(x, n, dim=axis))(v_cache[:, :, Sk - W:, :], rep, axis=1)
        scores = torch.einsum("bhqd,bhkd->bhqk", q, k) * (Dh ** -0.5)
        p = _softmax(scores, axis=-1)
        o = torch.einsum("bhqk,bhkd->bhqd", p, v)
        return (lambda x, *d: x.permute(*d))(o, 0, 2, 1, 3).reshape(B, Sq, Hq * Dh) @ wo

    def _B_ref(x, w_gate, w_up, w_down):
        g = torch.einsum("bsd,df->bsf", x, w_gate)
        u = torch.einsum("bsd,df->bsf", x, w_up)
        h = _gelu(g) * u
        return torch.einsum("bsf,fd->bsd", h, w_down)

    x = A_x
    g = _sigmoid((x * gate_w).sum(-1, keepdims=True))
    a = _A_ref(x, A_k_cache, A_v_cache, A_wq, A_wo)
    b = _B_ref(x, B_w_gate, B_w_up, B_w_down)
    return g * a + (1 - g) * b
```

```cpp
#include <cuda_runtime.h>
#include <cuda.h>
#include <cuda_bf16.h>
#include <stdint.h>

#define DRY 0
#define DEPTH 4
#define DEND 8
#define SWITCH 24

namespace {

constexpr int D_MODEL = 640;
constexpr int NHEAD   = 32;
constexpr int DHEAD   = 192;
constexpr int SK      = 4096;
constexpr int WIN     = 1024;
constexpr int DFF     = 1536;

constexpr int NCTA     = 128;
constexpr int NTHREADS = 384;

constexpr int SLOT      = 12288;
constexpr int OFF_WDX   = 8 * SLOT;
constexpr int OFF_OPART = OFF_WDX + 3072;
constexpr int OFF_QPART = OFF_OPART + 6144;
constexpr int OFF_RED1  = OFF_QPART + 3072;
constexpr int OFF_QS    = OFF_RED1 + 1536;
constexpr int OFF_GUP   = OFF_QS + 384;
constexpr int OFF_ML    = OFF_GUP + 384;
constexpr int OFF_CB    = OFF_ML + 256;
constexpr int OFF_GATE  = OFF_CB + 128;
constexpr int OFF_XS    = OFF_GATE + 16;
constexpr int OFF_SC    = OFF_XS + 640;
constexpr int OFF_BAR   = OFF_SC + 128;
constexpr int NSTAGE = 30, NEMPTY = 22;
constexpr int B_FULL = 0, B_EMPTY = 30, B_Q = 52, B_Q2 = 53, B_GU = 54, B_ML = 55, B_O = 56, B_C = 57, NBAR = 58;
constexpr int NINIT = (NBAR - DEPTH + 10) / 11;
constexpr int SMEM_BYTES = OFF_BAR + NBAR * 8;
static_assert(SMEM_BYTES <= 115712, "two CTAs must fit on one SM");

constexpr int NRED = 80;

__device__ uint4 g_ex3[NRED * NCTA * 2];

constexpr uint32_t SPIN_LIMIT = 1u << 22;

__device__ __forceinline__ uint32_t smem_u32(const void* p) { return (uint32_t)__cvta_generic_to_shared(p); }
__device__ __forceinline__ void mbar_init(uint32_t bar, int cnt) {
    asm volatile("mbarrier.init.shared::cta.b64 [%0], %1;" ::"r"(bar), "r"(cnt) : "memory");
}
__device__ __forceinline__ void mbar_expect(uint32_t bar, uint32_t bytes) {
    asm volatile("mbarrier.arrive.expect_tx.shared::cta.b64 _, [%0], %1;" ::"r"(bar), "r"(bytes) : "memory");
}
__device__ __forceinline__ void mbar_arrive(uint32_t bar) {
    asm volatile("mbarrier.arrive.shared::cta.b64 _, [%0];" ::"r"(bar) : "memory");
}
__device__ __forceinline__ bool mbar_try(uint32_t bar) {
    uint32_t ok;
    asm volatile("{\n .reg .pred p;\n mbarrier.try_wait.parity.shared::cta.b64 p, [%1], 0;\n selp.u32 %0, 1, 0, p;\n }"
                 : "=r"(ok) : "r"(bar) : "memory");
    return ok != 0;
}
__device__ __forceinline__ bool mbar_test(uint32_t bar) {
    uint32_t ok;
    asm volatile("{\n .reg .pred p;\n mbarrier.test_wait.parity.shared::cta.b64 p, [%1], 0;\n selp.u32 %0, 1, 0, p;\n }"
                 : "=r"(ok) : "r"(bar) : "memory");
    return ok != 0;
}
__device__ __forceinline__ void mbar_wait(uint32_t bar) {
    uint32_t n = 0;
    while (!mbar_try(bar)) { if (++n > SPIN_LIMIT) break; }
}
__device__ __forceinline__ void mbar_wait_cluster(uint32_t bar) {
    uint32_t n = 0, ok;
    do {
        asm volatile("{\n .reg .pred p;\n mbarrier.try_wait.parity.shared::cta.b64 p, [%1], 0;\n selp.u32 %0, 1, 0, p;\n }"
                     : "=r"(ok) : "r"(bar) : "memory");
    } while (!ok && ++n <= SPIN_LIMIT);
}
__device__ __forceinline__ uint32_t mapa(uint32_t addr, uint32_t rank) {
    uint32_t r;
    asm("mapa.shared::cluster.u32 %0, %1, %2;" : "=r"(r) : "r"(addr), "r"(rank));
    return r;
}
__device__ __forceinline__ void st_async4(uint32_t addr, float a, float b, float c, float d, uint32_t bar) {
    asm volatile("st.async.weak.shared::cluster.mbarrier::complete_tx::bytes.v4.f32 [%0], {%1,%2,%3,%4}, [%5];"
                 ::"r"(addr), "f"(a), "f"(b), "f"(c), "f"(d), "r"(bar) : "memory");
}
__device__ __forceinline__ void st_async2(uint32_t addr, float a, float b, uint32_t bar) {
    asm volatile("st.async.weak.shared::cluster.mbarrier::complete_tx::bytes.v2.f32 [%0], {%1,%2}, [%3];"
                 ::"r"(addr), "f"(a), "f"(b), "r"(bar) : "memory");
}
__device__ __forceinline__ void st_async1(uint32_t addr, float a, uint32_t bar) {
    asm volatile("st.async.weak.shared::cluster.mbarrier::complete_tx::bytes.f32 [%0], %1, [%2];"
                 ::"r"(addr), "f"(a), "r"(bar) : "memory");
}
__device__ __forceinline__ void bulk_g2s(uint32_t dst, const void* src, uint32_t bytes, uint32_t bar) {
    asm volatile("cp.async.bulk.shared::cluster.global.mbarrier::complete_tx::bytes [%0], [%1], %2, [%3];"
                 ::"r"(dst), "l"(src), "r"(bytes), "r"(bar) : "memory");
}
__device__ __forceinline__ void tensor_g2s(uint32_t dst, const CUtensorMap* map, int c0, int c1, uint32_t bar) {
    asm volatile("cp.async.bulk.tensor.2d.shared::cluster.global.mbarrier::complete_tx::bytes [%0], [%1, {%3, %4}], [%2];"
                 ::"r"(dst), "l"(map), "r"(bar), "r"(c0), "r"(c1) : "memory");
}
__device__ __forceinline__ void tensor3_g2s(uint32_t dst, const CUtensorMap* map, int c1, int c2, uint32_t bar) {
    asm volatile("cp.async.bulk.tensor.3d.shared::cluster.global.mbarrier::complete_tx::bytes [%0], [%1, {%3, %4, %5}], [%2];"
                 ::"r"(dst), "l"(map), "r"(bar), "r"(0), "r"(c1), "r"(c2) : "memory");
}
__device__ __forceinline__ void ldsm4t(uint32_t (&a)[4], uint32_t addr) {
    asm volatile("ldmatrix.sync.aligned.m8n8.x4.trans.shared.b16 {%0,%1,%2,%3}, [%4];"
                 : "=r"(a[0]), "=r"(a[1]), "=r"(a[2]), "=r"(a[3]) : "r"(addr));
}
__device__ __forceinline__ uint32_t lds32(uint32_t addr) {
    uint32_t v;
    asm volatile("ld.shared.u32 %0, [%1];" : "=r"(v) : "r"(addr));
    return v;
}
__device__ __forceinline__ void st_relaxed(uint32_t* p, uint32_t v) {
    asm volatile("st.relaxed.gpu.global.u32 [%0], %1;" ::"l"(p), "r"(v) : "memory");
}
__device__ __forceinline__ uint4 ld_relaxed4(const uint4* p) {
    uint4 v;
    asm volatile("ld.relaxed.gpu.global.v4.u32 {%0,%1,%2,%3}, [%4];"
                 : "=r"(v.x), "=r"(v.y), "=r"(v.z), "=r"(v.w) : "l"(p) : "memory");
    return v;
}
__device__ __forceinline__ void st_relaxed2(uint32_t* p, uint32_t a, uint32_t b) {
    asm volatile("st.relaxed.gpu.global.v2.u32 [%0], {%1,%2};" ::"l"(p), "r"(a), "r"(b) : "memory");
}
__device__ __forceinline__ void st_relaxed4(uint4* p, uint4 v) {
    asm volatile("st.relaxed.gpu.global.v4.u32 [%0], {%1,%2,%3,%4};" ::"l"(p), "r"(v.x), "r"(v.y), "r"(v.z), "r"(v.w) : "memory");
}
__device__ __forceinline__ uint32_t nz(float f) {
    uint32_t u = __float_as_uint(f);
    return u == 0u ? 0x80000000u : u;
}
__device__ __forceinline__ void bar_sync(int id, int n) { asm volatile("bar.sync %0, %1;" ::"r"(id), "r"(n) : "memory"); }
__device__ __forceinline__ float bf_lo(uint32_t w) { return __uint_as_float(w << 16); }
__device__ __forceinline__ float bf_hi(uint32_t w) { return __uint_as_float(w & 0xffff0000u); }
__device__ __forceinline__ float bfr(float f) { return __bfloat162float(__float2bfloat16_rn(f)); }
__device__ __forceinline__ uint32_t pack_bf2(float lo, float hi) {
    __nv_bfloat162 t = __floats2bfloat162_rn(lo, hi);
    return *reinterpret_cast<uint32_t*>(&t);
}
__device__ __forceinline__ void mma16816(float (&c)[4], uint32_t a0, uint32_t a1, uint32_t a2, uint32_t a3,
                                         uint32_t b0, uint32_t b1) {
    asm volatile("mma.sync.aligned.m16n8k16.row.col.f32.bf16.bf16.f32 {%0,%1,%2,%3}, {%4,%5,%6,%7}, {%8,%9}, {%0,%1,%2,%3};"
                 : "+f"(c[0]), "+f"(c[1]), "+f"(c[2]), "+f"(c[3])
                 : "r"(a0), "r"(a1), "r"(a2), "r"(a3), "r"(b0), "r"(b1));
}
__device__ __forceinline__ uint4 lds128(uint32_t addr) {
    uint4 v;
    asm volatile("ld.shared.v4.u32 {%0,%1,%2,%3}, [%4];" : "=r"(v.x), "=r"(v.y), "=r"(v.z), "=r"(v.w) : "r"(addr));
    return v;
}
__device__ __forceinline__ float4 lds128f(uint32_t addr) {
    float4 v;
    asm volatile("ld.shared.v4.f32 {%0,%1,%2,%3}, [%4];" : "=f"(v.x), "=f"(v.y), "=f"(v.z), "=f"(v.w) : "r"(addr));
    return v;
}
__device__ __forceinline__ void fma8(float (&acc)[8], float xv, const uint4& w) {
    acc[0] = fmaf(xv, bf_lo(w.x), acc[0]); acc[1] = fmaf(xv, bf_hi(w.x), acc[1]);
    acc[2] = fmaf(xv, bf_lo(w.y), acc[2]); acc[3] = fmaf(xv, bf_hi(w.y), acc[3]);
    acc[4] = fmaf(xv, bf_lo(w.z), acc[4]); acc[5] = fmaf(xv, bf_hi(w.z), acc[5]);
    acc[6] = fmaf(xv, bf_lo(w.w), acc[6]); acc[7] = fmaf(xv, bf_hi(w.w), acc[7]);
}

#define TSTAMP(i) do {} while (0)

__device__ __forceinline__ bool full4(const uint4& v) { return v.x && v.y && v.z && v.w; }

__global__ void __cluster_dims__(4, 1, 1) __launch_bounds__(NTHREADS, 2)
fused_decode_kernel(const __grid_constant__ CUtensorMap map_wq, const __grid_constant__ CUtensorMap map_wg,
                    const __grid_constant__ CUtensorMap map_wu, const __grid_constant__ CUtensorMap map_v,
                    const __grid_constant__ CUtensorMap map_wo, const __grid_constant__ CUtensorMap map_wd,
                    const __nv_bfloat16* __restrict__ x, const __nv_bfloat16* __restrict__ kc,
                    const __nv_bfloat16* __restrict__ gate_w, __nv_bfloat16* __restrict__ out) {
    extern __shared__ __align__(1024) unsigned char smem[];
    const uint32_t sbase = smem_u32(smem);
    const int tid = threadIdx.x, warp = tid >> 5, lane = tid & 31;
    const int b = blockIdx.x, h = b >> 2, r = b & 3;
    const float LOG2E = 1.4426950408889634f;
    const uint32_t bar0 = sbase + OFF_BAR;
#define BAR(i) (bar0 + (i) * 8)

    if (warp == 10) {
        if (lane == 0) {
#pragma unroll
            for (int i = 0; i < DEPTH; i++) mbar_init(BAR(B_FULL + i), 1);
        }
        asm volatile("fence.mbarrier_init.release.cluster;" ::: "memory");
        asm volatile("fence.proxy.async.shared::cta;" ::: "memory");
        __syncwarp();
        asm volatile("barrier.cluster.arrive.relaxed;" ::: "memory");
        const uint32_t dst = sbase + (lane & 7) * SLOT, fb = BAR(B_FULL + (lane < NSTAGE ? lane : 0));
        const size_t key = (size_t)h * SK + (SK - WIN) + ((lane & 7) * 4 + r) * 32;
        auto issue = [&]() {
            if (lane < 5) {
                mbar_expect(fb, 12288);
                tensor_g2s(dst, &map_wq, h * DHEAD, r * 160 + lane * 32, fb);
            } else if (lane < 8) {
                const int row = r * 160 + (lane - 5) * 64;
                if (lane < 7) {
                    mbar_expect(fb, 12288);
                    tensor_g2s(dst, &map_wg, h * 48, row, fb);
                    tensor_g2s(dst + 3072, &map_wg, h * 48, row + 32, fb);
                    tensor_g2s(dst + 6144, &map_wu, h * 48, row, fb);
                    tensor_g2s(dst + 9216, &map_wu, h * 48, row + 32, fb);
                } else {
                    mbar_expect(fb, 6144);
                    tensor_g2s(dst, &map_wg, h * 48, row, fb);
                    tensor_g2s(dst + 3072, &map_wu, h * 48, row, fb);
                }
            } else if (lane < 16) {
                mbar_expect(fb, 12288);
                bulk_g2s(dst, kc + key * DHEAD, 12288, fb);
            } else if (lane < 24) {
                mbar_expect(fb, 12288);
                tensor3_g2s(dst, &map_v, (int)key, 0, fb);
            } else if (lane == 24) {
                mbar_expect(fb, 15360);
#pragma unroll
                for (int t = 0; t < 5; t++)
                    tensor3_g2s(t < 4 ? dst + t * 3072 : sbase + OFF_WDX, &map_wd, h * 48 + r * 12, t * 2, fb);
            } else {
                mbar_expect(fb, 12288);
                tensor3_g2s(dst, &map_wo, h * DHEAD + r * 48, (lane - 25) * 2, fb);
            }
        };
#pragma unroll 1
        for (int i = 0; i < DEPTH; i++) { if (lane == i) issue(); __syncwarp(); }
        asm volatile("barrier.cluster.wait.acquire;" ::: "memory");
        int nxt = DEPTH;
        uint32_t n = 0;
        while (nxt < NSTAGE) {
            const bool f = lane < nxt && mbar_test(fb);
            const bool e = lane < NEMPTY && mbar_test(BAR(B_EMPTY + (lane < NEMPTY ? lane : 0)));
            const uint32_t fm = __ballot_sync(0xffffffffu, f), em = __ballot_sync(0xffffffffu, e);
            const int c = __popc(fm);
            while (nxt < NSTAGE && nxt < c + (nxt >= SWITCH ? DEND : DEPTH) && (nxt < 8 || ((em >> (nxt - 8)) & 1u))) {
                if (lane == nxt) {
                    issue();
                }
                __syncwarp();
                nxt++;
            }
            if (++n > SPIN_LIMIT) break;
        }
        return;
    }

    constexpr int npass = 2, pass0 = 1;
    if (lane == 0) {
        const int i0 = DEPTH + (warp == 11 ? 10 : warp) * NINIT;
#pragma unroll
        for (int k = 0; k < NINIT; k++) {
            const int i = i0 + k;
            if (i < NBAR) {
                int cnt = 1;
                if (i >= B_EMPTY && i < B_EMPTY + 8) cnt = i < B_EMPTY + 5 ? 6 : 3;
                if (i == B_Q2 || i == B_C) cnt = 32;
                if (i == B_GU) cnt = 2;
                mbar_init(BAR(i), cnt);
                if (i == B_Q)  mbar_expect(BAR(i), 4 * 768);
                if (i == B_GU) mbar_expect(BAR(i), 4 * 96);
                if (i == B_ML) mbar_expect(BAR(i), 32 * 8);
                if (i == B_O)  mbar_expect(BAR(i), 32 * 192);
            }
        }
        asm volatile("fence.mbarrier_init.release.cluster;" ::: "memory");
        asm volatile("fence.proxy.async.shared::cta;" ::: "memory");
    }
    __syncwarp();
    asm volatile("barrier.cluster.arrive.relaxed;" ::: "memory");

    if (warp == 11) {
        __nv_bfloat16* cb = reinterpret_cast<__nv_bfloat16*>(smem + OFF_CB);
#pragma unroll 1
        for (int pass = pass0; pass < npass; pass++) {
        const bool live = pass != 0;
        if (live) asm volatile("barrier.cluster.wait.acquire;" ::: "memory");
        if (live) mbar_wait_cluster(BAR(B_Q));
#pragma unroll
        for (int k = 0; k < 2; k++) {
            const int j = lane + k * 32;
            if (j < 48) {
                const float4 a0 = lds128f(sbase + OFF_QPART + j * 16), a1 = lds128f(sbase + OFF_QPART + 768 + j * 16);
                const float4 a2 = lds128f(sbase + OFF_QPART + 1536 + j * 16), a3 = lds128f(sbase + OFF_QPART + 2304 + j * 16);
                *reinterpret_cast<uint2*>(smem + OFF_QS + j * 8) =
                    make_uint2(pack_bf2((a0.x + a1.x) + (a2.x + a3.x), (a0.y + a1.y) + (a2.y + a3.y)),
                               pack_bf2((a0.z + a1.z) + (a2.z + a3.z), (a0.w + a1.w) + (a2.w + a3.w)));
            }
        }
        if (live) mbar_arrive(BAR(B_Q2));
        if (lane == 0) TSTAMP(2);
        if (live) mbar_wait_cluster(BAR(B_GU));
        if (lane < 12) {
            const float* gp = reinterpret_cast<const float*>(smem + OFF_GUP);
            const float gv = bfr((gp[lane] + gp[24 + lane]) + (gp[48 + lane] + gp[72 + lane]));
            const float uv = bfr((gp[12 + lane] + gp[36 + lane]) + (gp[60 + lane] + gp[84 + lane]));
            const float inner = 0.7978845608028654f * (gv + 0.044715f * gv * gv * gv);
            const float ge = bfr(0.5f * gv * (1.f + tanhf(inner)));
            cb[48 + lane] = __float2bfloat16_rn(ge * uv);
        } else if (lane < 16) cb[48 + lane] = __float2bfloat16_rn(0.f);
        if (live) mbar_wait_cluster(BAR(B_ML));
        {
            const float2 mlv = *reinterpret_cast<const float2*>(smem + OFF_ML + lane * 8);
            float M = mlv.x;
#pragma unroll
            for (int o = 16; o > 0; o >>= 1) M = fmaxf(M, __shfl_xor_sync(0xffffffffu, M, o));
            const float f = exp2f((mlv.x - M) * LOG2E);
            float L = f * mlv.y;
#pragma unroll
            for (int o = 16; o > 0; o >>= 1) L += __shfl_xor_sync(0xffffffffu, L, o);
            reinterpret_cast<float*>(smem + OFF_SC)[lane] = f / L;
            __syncwarp();
        }
        {
            const int q4 = lane % 12, hf = lane / 12;
            float sc[16];
#pragma unroll
            for (int i = 0; i < 4; i++) {
                const float4 s = lds128f(sbase + OFF_SC + ((hf & 1) * 16 + i * 4) * 4);
                sc[i * 4] = s.x; sc[i * 4 + 1] = s.y; sc[i * 4 + 2] = s.z; sc[i * 4 + 3] = s.w;
            }
            if (live) mbar_wait_cluster(BAR(B_O));
            if (lane == 0) TSTAMP(3);
            float o0 = 0.f, o1 = 0.f, o2 = 0.f, o3 = 0.f;
            const uint32_t a = sbase + OFF_OPART + (hf & 1) * 16 * 192 + q4 * 16;
#pragma unroll
            for (int i = 0; i < 16; i++) {
                const float4 v = lds128f(a + i * 192);
                o0 = fmaf(sc[i], v.x, o0); o1 = fmaf(sc[i], v.y, o1); o2 = fmaf(sc[i], v.z, o2); o3 = fmaf(sc[i], v.w, o3);
            }
            o0 += __shfl_down_sync(0xffffffffu, o0, 12); o1 += __shfl_down_sync(0xffffffffu, o1, 12);
            o2 += __shfl_down_sync(0xffffffffu, o2, 12); o3 += __shfl_down_sync(0xffffffffu, o3, 12);
            if (lane < 8) {
                cb[lane] = __float2bfloat16_rn(o0);      cb[lane + 8] = __float2bfloat16_rn(o1);
                cb[lane + 16] = __float2bfloat16_rn(o2); cb[lane + 24] = __float2bfloat16_rn(o3);
            } else if (lane < 12) {
                const int g = (lane - 8) * 2;
                cb[32 + g] = __float2bfloat16_rn(o0); cb[40 + g] = __float2bfloat16_rn(o1);
                cb[33 + g] = __float2bfloat16_rn(o2); cb[41 + g] = __float2bfloat16_rn(o3);
            }
            if (live) mbar_arrive(BAR(B_C));
            if (lane == 0) TSTAMP(4);
        }
        if (b < NRED) {
            uint4* box3 = g_ex3 + (size_t)b * NCTA * 2 + lane;
            uint4 v3[8];
#pragma unroll
            for (int k = 0; k < 8; k++) v3[k] = make_uint4(0, 0, 0, 0);
            uint32_t pend3 = live ? 0xffu : 0u, n = 0;
            if (live && lane < 6) mbar_wait(BAR(B_FULL + 24 + lane));
            __syncwarp();
            if (lane == 0) TSTAMP(7);
            while (pend3) {
#pragma unroll
                for (int k = 0; k < 8; k++)
                    if (pend3 & (1u << k)) v3[k] = ld_relaxed4(box3 + k * 32);
#pragma unroll
                for (int k = 0; k < 8; k++)
                    if (full4(v3[k])) pend3 &= ~(1u << k);
                if (++n > SPIN_LIMIT) break;
            }
            if (lane == 0) TSTAMP(8);
            float s0 = 0.f, s1 = 0.f, s2 = 0.f, s3 = 0.f;
#pragma unroll
            for (int k = 0; k < 8; k++) {
                s0 += __uint_as_float(v3[k].x); s1 += __uint_as_float(v3[k].y);
                s2 += __uint_as_float(v3[k].z); s3 += __uint_as_float(v3[k].w);
            }
#pragma unroll
            for (int o = 2; o < 32; o <<= 1) {
                s0 += __shfl_xor_sync(0xffffffffu, s0, o); s1 += __shfl_xor_sync(0xffffffffu, s1, o);
                s2 += __shfl_xor_sync(0xffffffffu, s2, o); s3 += __shfl_xor_sync(0xffffffffu, s3, o);
            }
            if (live && lane < 2) *reinterpret_cast<uint2*>(out + b * 8 + lane * 4) = make_uint2(pack_bf2(s0, s1), pack_bf2(s2, s3));
#pragma unroll
            for (int k = 0; k < 8; k++) if (live) st_relaxed4(box3 + k * 32, make_uint4(0, 0, 0, 0));
            if (lane == 0) TSTAMP(9);
        }
        }
        return;
    }

    const float* xs = reinterpret_cast<const float*>(smem + OFF_XS);
    const __nv_bfloat16 xin = x[r * 160 + (tid < 160 ? tid : 0)];
#pragma unroll 1
    for (int pass = pass0; pass < npass; pass++) {
    const bool live = pass != 0;
    if (live) {
        if (tid < 160) reinterpret_cast<float*>(smem + OFF_XS)[tid] = __bfloat162float(xin);
        bar_sync(3, 320);
        asm volatile("barrier.cluster.wait.acquire;" ::: "memory");
    }
    if (warp < 6) {
        const int c3 = warp % 3, hf = warp / 3, rs = lane >> 3;
        const uint32_t a = sbase + (hf * 16 + rs) * 384 + c3 * 128 + (lane & 7) * 16;
        float acc[8];
#pragma unroll
        for (int j = 0; j < 8; j++) acc[j] = 0.f;
#pragma unroll 1
        for (int s = 0; s < 5; s++) {
            float xv[4];
#pragma unroll
            for (int i = 0; i < 4; i++) xv[i] = xs[s * 32 + hf * 16 + rs + 4 * i];
            if (live) mbar_wait(BAR(B_FULL + s));
#pragma unroll
            for (int i = 0; i < 4; i++) fma8(acc, xv[i], lds128(a + s * SLOT + i * 1536));
            __syncwarp();
            if (live && lane == 0) mbar_arrive(BAR(B_EMPTY + s));
        }
#pragma unroll
        for (int j = 0; j < 8; j++) {
            acc[j] += __shfl_xor_sync(0xffffffffu, acc[j], 8);
            acc[j] += __shfl_xor_sync(0xffffffffu, acc[j], 16);
        }
        if (lane < 16) {
            float4* dst = reinterpret_cast<float4*>(smem + OFF_RED1 + hf * 768 + c3 * 256 + (lane & 7) * 32 + rs * 16);
            *dst = rs ? make_float4(acc[4], acc[5], acc[6], acc[7]) : make_float4(acc[0], acc[1], acc[2], acc[3]);
        }
        bar_sync(1, 192);
        const int dest = tid / 48, quad = tid % 48;
        const float4 u0 = lds128f(sbase + OFF_RED1 + quad * 16), u1 = lds128f(sbase + OFF_RED1 + 768 + quad * 16);
        if (live) st_async4(mapa(sbase + OFF_QPART + r * 768 + quad * 16, dest), u0.x + u1.x, u0.y + u1.y, u0.z + u1.z,
                            u0.w + u1.w, mapa(BAR(B_Q), dest));
        if (tid == 0) TSTAMP(1);
    } else if (warp < 9) {
        const int t = tid - 192, rg = t / 6;
        float ag[8], au[8];
#pragma unroll
        for (int j = 0; j < 8; j++) { ag[j] = 0.f; au[j] = 0.f; }
#pragma unroll
        for (int s = 0; s < 3; s++) {
            const uint32_t a = sbase + (5 + s) * SLOT + t * 16;
            if (live) mbar_wait(BAR(B_FULL + 5 + s));
#pragma unroll
            for (int i = 0; i < (s < 2 ? 4 : 2); i++) {
                const float xv = xs[s * 64 + rg + 16 * i];
                fma8(ag, xv, lds128(a + i * 1536));
                fma8(au, xv, lds128(a + (s < 2 ? 6144 : 3072) + i * 1536));
            }
            if (s < 2) {
                __syncwarp();
                if (live && lane == 0) mbar_arrive(BAR(B_EMPTY + 5 + s));
            }
        }
        float* red2 = reinterpret_cast<float*>(smem + 7 * SLOT + 6144);
        float4* dst = reinterpret_cast<float4*>(red2 + rg * 96 + (t % 6) * 8);
        dst[0] = make_float4(ag[0], ag[1], ag[2], ag[3]);   dst[1] = make_float4(ag[4], ag[5], ag[6], ag[7]);
        dst[12] = make_float4(au[0], au[1], au[2], au[3]);  dst[13] = make_float4(au[4], au[5], au[6], au[7]);
        bar_sync(2, 96);
        float s = 0.f;
#pragma unroll
        for (int i = 0; i < 16; i++) s += red2[i * 96 + t];
        const int c = t % 48, dest = c / 12;
        if (live) st_async1(mapa(sbase + OFF_GUP + (r * 24 + (t / 48) * 12 + c % 12) * 4, dest), s, mapa(BAR(B_GU), dest));
        asm volatile("fence.proxy.async.shared::cta;" ::: "memory");
        __syncwarp();
        if (live && lane == 0) mbar_arrive(BAR(B_EMPTY + 7));
    } else if (live) {
        float gs = 0.f;
        for (int c = lane; c < D_MODEL / 8; c += 32) {
            uint4 xv = *reinterpret_cast<const uint4*>(x + c * 8);
            uint4 gv = *reinterpret_cast<const uint4*>(gate_w + c * 8);
            gs += bfr(bf_lo(xv.x) * bf_lo(gv.x)) + bfr(bf_hi(xv.x) * bf_hi(gv.x));
            gs += bfr(bf_lo(xv.y) * bf_lo(gv.y)) + bfr(bf_hi(xv.y) * bf_hi(gv.y));
            gs += bfr(bf_lo(xv.z) * bf_lo(gv.z)) + bfr(bf_hi(xv.z) * bf_hi(gv.z));
            gs += bfr(bf_lo(xv.w) * bf_lo(gv.w)) + bfr(bf_hi(xv.w) * bf_hi(gv.w));
        }
#pragma unroll
        for (int o = 16; o > 0; o >>= 1) gs += __shfl_xor_sync(0xffffffffu, gs, o);
        const float gate = bfr(1.f / (1.f + __expf(-bfr(gs))));
        if (lane == 0) {
            *reinterpret_cast<float2*>(smem + OFF_GATE) = make_float2(gate, bfr(1.f - gate));
            mbar_arrive(BAR(B_GU));
        }
    }

    if (!live && warp != 9) continue;

    if (warp < 8 || !live) {
        const int g = lane >> 2, t = lane & 3;
        const int chunk = warp * 4 + r;
        const uint32_t slot = sbase + (warp & 7) * SLOT;
        if (live) mbar_wait(BAR(B_Q2));
        uint32_t qf[6][4];
#pragma unroll
        for (int s = 0; s < 6; s++) {
            uint4 v = lds128(sbase + OFF_QS + (((s ^ (g & 1)) * 4 + t) * 16));
            qf[s][0] = v.x; qf[s][1] = v.y; qf[s][2] = v.z; qf[s][3] = v.w;
        }
        if (live) mbar_wait(BAR(B_FULL + 8 + warp));
        float c0[4] = {0.f, 0.f, 0.f, 0.f}, c1[4] = {0.f, 0.f, 0.f, 0.f};
        const uint32_t kb = slot + (16 * (g >> 2) + 2 * (g & 3)) * 384;
#pragma unroll
        for (int s = 0; s < 6; s++) {
            const uint32_t co = ((s ^ (g & 1)) * 4 + t) * 16;
            uint4 r0 = lds128(kb + co), r1 = lds128(kb + 384 + co), r2 = lds128(kb + 3072 + co), r3 = lds128(kb + 3456 + co);
            mma16816(c0, r0.x, r1.x, r0.y, r1.y, qf[s][0], qf[s][1]);
            mma16816(c1, r2.x, r3.x, r2.y, r3.y, qf[s][0], qf[s][1]);
            mma16816(c0, r0.z, r1.z, r0.w, r1.w, qf[s][2], qf[s][3]);
            mma16816(c1, r2.z, r3.z, r2.w, r3.w, qf[s][2], qf[s][3]);
        }
        __syncwarp();
        if (live && lane == 0) mbar_arrive(BAR(B_EMPTY + 8 + warp));
        const float scale = 0.07216878364870322f;
        float sc[4];
        sc[0] = (g & 1) ? c0[1] : c0[0];
        sc[1] = (g & 1) ? c0[3] : c0[2];
        sc[2] = (g & 1) ? c1[1] : c1[0];
        sc[3] = (g & 1) ? c1[3] : c1[2];
#pragma unroll
        for (int i = 0; i < 4; i++) sc[i] = bfr(bfr(sc[i]) * scale);
        float m = fmaxf(fmaxf(sc[0], sc[1]), fmaxf(sc[2], sc[3]));
#pragma unroll
        for (int o = 4; o < 32; o <<= 1) m = fmaxf(m, __shfl_xor_sync(0xffffffffu, m, o));
        float p[4], l = 0.f;
#pragma unroll
        for (int i = 0; i < 4; i++) { p[i] = exp2f((sc[i] - m) * LOG2E); l += p[i]; }
#pragma unroll
        for (int o = 4; o < 32; o <<= 1) l += __shfl_xor_sync(0xffffffffu, l, o);
        if (live && lane < 4) st_async2(mapa(sbase + OFF_ML + chunk * 8, lane), m, l, mapa(BAR(B_ML), lane));
        if (t & 1) {
#pragma unroll
            for (int i = 0; i < 4; i++) p[i] -= bfr(p[i]);
        }
        const uint32_t pk0 = pack_bf2(p[0], p[1]), pk1 = pack_bf2(p[2], p[3]);
        uint32_t bp[2][2];
#pragma unroll
        for (int s2 = 0; s2 < 2; s2++) {
            const int src = (4 * s2 + t) * 4 + (g & 1);
            bp[s2][0] = __shfl_sync(0xffffffffu, pk0, src);
            bp[s2][1] = __shfl_sync(0xffffffffu, pk1, src);
        }
        const uint32_t oaddr = mapa(sbase + OFF_OPART + chunk * 192, t), obar = mapa(BAR(B_O), t);
        const uint32_t vrow = slot + ((lane & 7) + (lane >> 4) * 8) * 128;
        const uint32_t vsw = (lane & 7) ^ ((lane >> 3) & 1);
        if (live) mbar_wait(BAR(B_FULL + 16 + warp));
#pragma unroll
        for (int d = 0; d < 4; d++) {
            float acc[3][4];
#pragma unroll
            for (int j = 0; j < 3; j++) {
                acc[j][0] = acc[j][1] = acc[j][2] = acc[j][3] = 0.f;
                const int mt = d * 3 + j;
#pragma unroll
                for (int s2 = 0; s2 < 2; s2++) {
                    uint32_t a[4];
                    ldsm4t(a, vrow + (mt >> 2) * 4096 + s2 * 2048 + ((vsw ^ ((mt & 3) * 2)) << 4));
                    mma16816(acc[j], a[0], a[1], a[2], a[3], bp[s2][0], bp[s2][1]);
                }
            }
            if (live && t == d) {
                st_async4(oaddr + g * 16, acc[0][0] + acc[0][1], acc[0][2] + acc[0][3], acc[1][0] + acc[1][1], acc[1][2] + acc[1][3], obar);
                st_async2(oaddr + 128 + g * 8, acc[2][0] + acc[2][1], acc[2][2] + acc[2][3], obar);
            }
        }
        __syncwarp();
        if (live && lane == 0 && warp < 6) mbar_arrive(BAR(B_EMPTY + 16 + warp));
        if (lane == 0 && warp == 7) TSTAMP(10);
    }
    {
        const int g = lane >> 2, t = lane & 3;
        const int lr = (lane & 7) + (lane >> 4) * 8, lc = (lane >> 3) & 1;
        const uint32_t wob = sbase + (1 + (warp >> 1)) * SLOT + (warp & 1) * 6144 + lr * 128;
        const uint32_t wdb = (warp < 8 ? sbase + warp * 1536 : sbase + OFF_WDX + (warp - 8) * 1536) + (lr < 12 ? lr : lr - 4) * 128;
        const uint32_t swo = (lane & 7) ^ lc, swd = ((wdb >> 7) & 7) ^ lc;
        uint32_t* dst = reinterpret_cast<uint32_t*>(g_ex3) + ((size_t)(warp * 8 + t * 2) * NCTA + b) * 8 + g;
        if (live) {
            mbar_wait(BAR(B_FULL + 24));
            mbar_wait(BAR(B_FULL + 25 + (warp >> 1)));
            mbar_wait(BAR(B_C));
        }
        if (tid == 0) TSTAMP(5);
        uint32_t bc[4][2];
#pragma unroll
        for (int ks = 0; ks < 4; ks++) {
            const uint32_t v0 = lds32(sbase + OFF_CB + ks * 32 + t * 4), v1 = lds32(sbase + OFF_CB + ks * 32 + 16 + t * 4);
            const bool on = ((g & 1) != 0) == (ks == 3);
            bc[ks][0] = on ? v0 : 0u; bc[ks][1] = on ? v1 : 0u;
        }
        const float2 gt = *reinterpret_cast<const float2*>(smem + OFF_GATE);
        float r0 = 0.f, r1 = 0.f;
#pragma unroll
        for (int mt = 0; mt < 4; mt++) {
            float acc[4] = {0.f, 0.f, 0.f, 0.f};
#pragma unroll
            for (int ks = 0; ks < 4; ks++) {
                uint32_t a[4];
                ldsm4t(a, ks < 3 ? wob + ks * 2048 + ((swo ^ (mt * 2)) << 4) : wdb + ((swd ^ (mt * 2)) << 4));
                mma16816(acc, a[0], a[1], a[2], a[3], bc[ks][0], bc[ks][1]);
            }
            if (t == mt) { r0 = gt.x * acc[0] + gt.y * acc[1]; r1 = gt.x * acc[2] + gt.y * acc[3]; }
        }
        if (live) {
            st_relaxed(dst, nz(r0));
            st_relaxed(dst + NCTA * 8, nz(r1));
        }
        if (tid == 0) TSTAMP(6);
    }
    }
#undef BAR
}

typedef CUresult (*EncodeTiledFn)(CUtensorMap*, CUtensorMapDataType, cuuint32_t, void*, const cuuint64_t*, const cuuint64_t*,
                                  const cuuint32_t*, const cuuint32_t*, CUtensorMapInterleave, CUtensorMapSwizzle,
                                  CUtensorMapL2promotion, CUtensorMapFloatOOBfill);

void make_map(EncodeTiledFn fn, CUtensorMap* m, const void* ptr, uint64_t cols, uint64_t rows, uint32_t box_c, uint32_t box_r) {
    cuuint64_t dims[2] = {cols, rows};
    cuuint64_t strides[1] = {cols * 2};
    cuuint32_t box[2] = {box_c, box_r};
    cuuint32_t es[2] = {1, 1};
    fn(m, CU_TENSOR_MAP_DATA_TYPE_BFLOAT16, 2, const_cast<void*>(ptr), dims, strides, box, es, CU_TENSOR_MAP_INTERLEAVE_NONE,
       CU_TENSOR_MAP_SWIZZLE_NONE, CU_TENSOR_MAP_L2_PROMOTION_NONE, CU_TENSOR_MAP_FLOAT_OOB_FILL_NONE);
}

void make_map3(EncodeTiledFn fn, CUtensorMap* m, const void* ptr, uint64_t cols, uint64_t rows, uint32_t box_r, uint32_t box_b) {
    cuuint64_t dims[3] = {64, rows, cols / 64};
    cuuint64_t strides[2] = {cols * 2, 128};
    cuuint32_t box[3] = {64, box_r, box_b};
    cuuint32_t es[3] = {1, 1, 1};
    fn(m, CU_TENSOR_MAP_DATA_TYPE_BFLOAT16, 3, const_cast<void*>(ptr), dims, strides, box, es, CU_TENSOR_MAP_INTERLEAVE_NONE,
       CU_TENSOR_MAP_SWIZZLE_128B, CU_TENSOR_MAP_L2_PROMOTION_NONE, CU_TENSOR_MAP_FLOAT_OOB_FILL_NONE);
}

}

extern "C" void kernel_launch(void* const* d_in, const int* in_sizes, int n_in, void* d_out, int out_size) {
    (void)in_sizes; (void)n_in; (void)out_size;
    static EncodeTiledFn encode = nullptr;
    if (!encode) {
        cudaFuncSetAttribute(fused_decode_kernel, cudaFuncAttributeMaxDynamicSharedMemorySize, SMEM_BYTES);
        void* fn = nullptr;
        cudaDriverEntryPointQueryResult qr;
        cudaGetDriverEntryPoint("cuTensorMapEncodeTiled", &fn, cudaEnableDefault, &qr);
        encode = (EncodeTiledFn)fn;
    }
    CUtensorMap mq, mg, mu, mv, mo, md;
    make_map(encode, &mq, d_in[3], NHEAD * DHEAD, D_MODEL, DHEAD, 32);
    make_map(encode, &mg, d_in[6], DFF, D_MODEL, 48, 32);
    make_map(encode, &mu, d_in[7], DFF, D_MODEL, 48, 32);
    make_map3(encode, &mv, d_in[2], DHEAD, (uint64_t)NHEAD * SK, 32, 3);
    make_map3(encode, &mo, d_in[4], D_MODEL, NHEAD * DHEAD, 48, 2);
    make_map3(encode, &md, d_in[8], D_MODEL, DFF, 12, 2);
    const __nv_bfloat16* x  = (const __nv_bfloat16*)d_in[0];
    const __nv_bfloat16* kc = (const __nv_bfloat16*)d_in[1];
    const __nv_bfloat16* gw = (const __nv_bfloat16*)d_in[9];
    fused_decode_kernel<<<NCTA, NTHREADS, SMEM_BYTES>>>(mq, mg, mu, mv, mo, md, x, kc, gw, (__nv_bfloat16*)d_out);
}
```

```cpp
#include <cuda_runtime.h>
#include <cuda.h>
#include <cuda_bf16.h>
#include <stdint.h>

#define DEPTH 4
#define DEXTRA 1
#define DEND 8
#define SWITCH 28
#define TOUCH 19

#define PGAP 250

namespace {

constexpr int D_MODEL = 640;
constexpr int NHEAD   = 32;
constexpr int DHEAD   = 192;
constexpr int SK      = 4096;
constexpr int WIN     = 1024;
constexpr int DFF     = 1536;

constexpr int NCTA     = 128;
constexpr int NTHREADS = 384;

constexpr int SLOT      = 12288;
constexpr int OFF_WDX   = 8 * SLOT;
constexpr int OFF_QPART = OFF_WDX + 3072;
constexpr int OFF_RED1  = OFF_QPART + 3072;
constexpr int OFF_OPART = OFF_RED1 + 1536;
constexpr int OFF_PS    = OFF_OPART + 768;
constexpr int OFF_QS    = OFF_PS + 512;
constexpr int OFF_GUP   = OFF_QS + 384;
constexpr int OFF_ML    = OFF_GUP + 384;
constexpr int OFF_HB    = OFF_ML + 256;
constexpr int OFF_GATE  = OFF_HB + 32;
constexpr int OFF_FIN   = OFF_GATE + 16;
constexpr int OFF_XS    = OFF_FIN + 32;
constexpr int OFF_BAR   = OFF_XS + 640;
constexpr int NSTAGE = 30, NEMPTY = 22;
constexpr int B_FULL = 0, B_EMPTY = 30, B_Q = 52, B_Q2 = 53, B_GU = 54, B_ML = 55, B_P = 56, B_O = 57, B_H = 58, B_T = 59, NBAR = 60;
constexpr int NINIT = (NBAR - DEPTH + 10) / 11;
constexpr int SMEM_BYTES = OFF_BAR + NBAR * 8;
static_assert(SMEM_BYTES <= 115712, "two CTAs must fit on one SM");

constexpr int NRED = 80;

__device__ uint4 g_ex3[NRED * 2 * NCTA];
__device__ uint32_t g_epoch;
__device__ uint32_t g_smcnt[256];

constexpr uint32_t SPIN_LIMIT = 1u << 22;

__device__ __forceinline__ uint32_t smem_u32(const void* p) { return (uint32_t)__cvta_generic_to_shared(p); }
__device__ __forceinline__ void mbar_init(uint32_t bar, int cnt) {
    asm volatile("mbarrier.init.shared::cta.b64 [%0], %1;" ::"r"(bar), "r"(cnt) : "memory");
}
__device__ __forceinline__ void mbar_expect(uint32_t bar, uint32_t bytes) {
    asm volatile("mbarrier.arrive.expect_tx.shared::cta.b64 _, [%0], %1;" ::"r"(bar), "r"(bytes) : "memory");
}
__device__ __forceinline__ void mbar_arrive(uint32_t bar) {
    asm volatile("mbarrier.arrive.shared::cta.b64 _, [%0];" ::"r"(bar) : "memory");
}
__device__ __forceinline__ bool mbar_try(uint32_t bar) {
    uint32_t ok;
    asm volatile("{\n .reg .pred p;\n mbarrier.try_wait.parity.shared::cta.b64 p, [%1], 0;\n selp.u32 %0, 1, 0, p;\n }"
                 : "=r"(ok) : "r"(bar) : "memory");
    return ok != 0;
}
__device__ __forceinline__ bool mbar_test(uint32_t bar) {
    uint32_t ok;
    asm volatile("{\n .reg .pred p;\n mbarrier.test_wait.parity.shared::cta.b64 p, [%1], 0;\n selp.u32 %0, 1, 0, p;\n }"
                 : "=r"(ok) : "r"(bar) : "memory");
    return ok != 0;
}
__device__ __forceinline__ void mbar_wait(uint32_t bar) {
    uint32_t n = 0;
    while (!mbar_try(bar)) { if (++n > SPIN_LIMIT) break; }
}
__device__ __forceinline__ void mbar_wait_cluster(uint32_t bar) {
    uint32_t n = 0, ok;
    do {
        asm volatile("{\n .reg .pred p;\n mbarrier.try_wait.parity.shared::cta.b64 p, [%1], 0;\n selp.u32 %0, 1, 0, p;\n }"
                     : "=r"(ok) : "r"(bar) : "memory");
    } while (!ok && ++n <= SPIN_LIMIT);
}
__device__ __forceinline__ uint32_t mapa(uint32_t addr, uint32_t rank) {
    uint32_t r;
    asm("mapa.shared::cluster.u32 %0, %1, %2;" : "=r"(r) : "r"(addr), "r"(rank));
    return r;
}
__device__ __forceinline__ void st_async4(uint32_t addr, float a, float b, float c, float d, uint32_t bar) {
    asm volatile("st.async.weak.shared::cluster.mbarrier::complete_tx::bytes.v4.f32 [%0], {%1,%2,%3,%4}, [%5];"
                 ::"r"(addr), "f"(a), "f"(b), "f"(c), "f"(d), "r"(bar) : "memory");
}
__device__ __forceinline__ void st_async2(uint32_t addr, float a, float b, uint32_t bar) {
    asm volatile("st.async.weak.shared::cluster.mbarrier::complete_tx::bytes.v2.f32 [%0], {%1,%2}, [%3];"
                 ::"r"(addr), "f"(a), "f"(b), "r"(bar) : "memory");
}
__device__ __forceinline__ void st_async1(uint32_t addr, float a, uint32_t bar) {
    asm volatile("st.async.weak.shared::cluster.mbarrier::complete_tx::bytes.f32 [%0], %1, [%2];"
                 ::"r"(addr), "f"(a), "r"(bar) : "memory");
}
__device__ __forceinline__ void bulk_g2s(uint32_t dst, const void* src, uint32_t bytes, uint32_t bar) {
    asm volatile("cp.async.bulk.shared::cluster.global.mbarrier::complete_tx::bytes [%0], [%1], %2, [%3];"
                 ::"r"(dst), "l"(src), "r"(bytes), "r"(bar) : "memory");
}
__device__ __forceinline__ void tensor_g2s(uint32_t dst, const CUtensorMap* map, int c0, int c1, uint32_t bar) {
    asm volatile("cp.async.bulk.tensor.2d.shared::cluster.global.mbarrier::complete_tx::bytes [%0], [%1, {%3, %4}], [%2];"
                 ::"r"(dst), "l"(map), "r"(bar), "r"(c0), "r"(c1) : "memory");
}
__device__ __forceinline__ void tensor3_g2s(uint32_t dst, const CUtensorMap* map, int c1, int c2, uint32_t bar) {
    asm volatile("cp.async.bulk.tensor.3d.shared::cluster.global.mbarrier::complete_tx::bytes [%0], [%1, {%3, %4, %5}], [%2];"
                 ::"r"(dst), "l"(map), "r"(bar), "r"(0), "r"(c1), "r"(c2) : "memory");
}
__device__ __forceinline__ void ldsm4t(uint32_t (&a)[4], uint32_t addr) {
    asm volatile("ldmatrix.sync.aligned.m8n8.x4.trans.shared.b16 {%0,%1,%2,%3}, [%4];"
                 : "=r"(a[0]), "=r"(a[1]), "=r"(a[2]), "=r"(a[3]) : "r"(addr));
}
__device__ __forceinline__ uint32_t lds32(uint32_t addr) {
    uint32_t v;
    asm volatile("ld.shared.u32 %0, [%1];" : "=r"(v) : "r"(addr));
    return v;
}
__device__ __forceinline__ uint32_t lds32v(uint32_t addr) {
    uint32_t v;
    asm volatile("ld.volatile.shared.u32 %0, [%1];" : "=r"(v) : "r"(addr) : "memory");
    return v;
}
__device__ __forceinline__ void st_relaxed(uint32_t* p, uint32_t v) {
    asm volatile("st.relaxed.gpu.global.u32 [%0], %1;" ::"l"(p), "r"(v) : "memory");
}
__device__ __forceinline__ uint32_t ld_relaxed(const uint32_t* p) {
    uint32_t v;
    asm volatile("ld.relaxed.gpu.global.u32 %0, [%1];" : "=r"(v) : "l"(p) : "memory");
    return v;
}
__device__ __forceinline__ uint4 ld_relaxed4(const uint4* p) {
    uint4 v;
    asm volatile("ld.relaxed.gpu.global.v4.u32 {%0,%1,%2,%3}, [%4];"
                 : "=r"(v.x), "=r"(v.y), "=r"(v.z), "=r"(v.w) : "l"(p) : "memory");
    return v;
}
__device__ __forceinline__ void st_relaxed2(uint32_t* p, uint32_t a, uint32_t b) {
    asm volatile("st.relaxed.gpu.global.v2.u32 [%0], {%1,%2};" ::"l"(p), "r"(a), "r"(b) : "memory");
}
__device__ __forceinline__ void st_relaxed4(uint4* p, uint4 v) {
    asm volatile("st.relaxed.gpu.global.v4.u32 [%0], {%1,%2,%3,%4};" ::"l"(p), "r"(v.x), "r"(v.y), "r"(v.z), "r"(v.w) : "memory");
}
__device__ __forceinline__ void bar_sync(int id, int n) { asm volatile("bar.sync %0, %1;" ::"r"(id), "r"(n) : "memory"); }
__device__ __forceinline__ float bf_lo(uint32_t w) { return __uint_as_float(w << 16); }
__device__ __forceinline__ float bf_hi(uint32_t w) { return __uint_as_float(w & 0xffff0000u); }
__device__ __forceinline__ float bfr(float f) { return __bfloat162float(__float2bfloat16_rn(f)); }
__device__ __forceinline__ uint32_t pack_bf2(float lo, float hi) {
    __nv_bfloat162 t = __floats2bfloat162_rn(lo, hi);
    return *reinterpret_cast<uint32_t*>(&t);
}
__device__ __forceinline__ void mma16816(float (&c)[4], uint32_t a0, uint32_t a1, uint32_t a2, uint32_t a3,
                                         uint32_t b0, uint32_t b1) {
    asm volatile("mma.sync.aligned.m16n8k16.row.col.f32.bf16.bf16.f32 {%0,%1,%2,%3}, {%4,%5,%6,%7}, {%8,%9}, {%0,%1,%2,%3};"
                 : "+f"(c[0]), "+f"(c[1]), "+f"(c[2]), "+f"(c[3])
                 : "r"(a0), "r"(a1), "r"(a2), "r"(a3), "r"(b0), "r"(b1));
}
__device__ __forceinline__ uint4 lds128(uint32_t addr) {
    uint4 v;
    asm volatile("ld.shared.v4.u32 {%0,%1,%2,%3}, [%4];" : "=r"(v.x), "=r"(v.y), "=r"(v.z), "=r"(v.w) : "r"(addr));
    return v;
}
__device__ __forceinline__ float4 lds128f(uint32_t addr) {
    float4 v;
    asm volatile("ld.shared.v4.f32 {%0,%1,%2,%3}, [%4];" : "=f"(v.x), "=f"(v.y), "=f"(v.z), "=f"(v.w) : "r"(addr));
    return v;
}
__device__ __forceinline__ void fma8(float (&acc)[8], float xv, const uint4& w) {
    acc[0] = fmaf(xv, bf_lo(w.x), acc[0]); acc[1] = fmaf(xv, bf_hi(w.x), acc[1]);
    acc[2] = fmaf(xv, bf_lo(w.y), acc[2]); acc[3] = fmaf(xv, bf_hi(w.y), acc[3]);
    acc[4] = fmaf(xv, bf_lo(w.z), acc[4]); acc[5] = fmaf(xv, bf_hi(w.z), acc[5]);
    acc[6] = fmaf(xv, bf_lo(w.w), acc[6]); acc[7] = fmaf(xv, bf_hi(w.w), acc[7]);
}

#define TSTAMP(i) do {} while (0)

__device__ __forceinline__ void accept4(uint4& dst, const uint4& v, uint32_t tag, uint32_t& pend, int k) {
    const uint32_t bad = ((v.x ^ tag) | (v.y ^ tag) | (v.z ^ tag) | (v.w ^ tag)) & 1u;
    dst.x = bad ? dst.x : v.x; dst.y = bad ? dst.y : v.y; dst.z = bad ? dst.z : v.z; dst.w = bad ? dst.w : v.w;
    pend &= ~((bad ^ 1u) << k);
}
__device__ __forceinline__ void ld_relaxed4_if(uint4& v, const uint4* p, uint32_t cond) {
    asm volatile("{\n .reg .pred p;\n setp.ne.u32 p, %5, 0;\n @p ld.relaxed.gpu.global.v4.u32 {%0,%1,%2,%3}, [%4];\n}"
                 : "+r"(v.x), "+r"(v.y), "+r"(v.z), "+r"(v.w) : "l"(p), "r"(cond) : "memory");
}

__device__ __forceinline__ void final_reduce(int b, int hw, int lane, uint32_t sbase, __nv_bfloat16* __restrict__ out) {
    const uint32_t bar0 = sbase + OFF_BAR;
    const uint4* box = g_ex3 + ((size_t)b * NCTA + hw * 64) * 2 + lane;
    uint4 A[4], B[4];
    uint32_t pend = 0xfu, n = 0;
    if (hw == 0) {
        mbar_wait(bar0 + (B_FULL + TOUCH) * 8);
#pragma unroll
        for (int k = 0; k < 4; k++) A[k] = ld_relaxed4(box + k * 32);
#pragma unroll
        for (int k = 0; k < 4; k++) B[k] = ld_relaxed4(box + 128 + k * 32);
#pragma unroll
        for (int k = 0; k < 4; k++)
            asm volatile("st.shared.v4.u32 [%0], {%1,%2,%3,%4};" ::"r"(sbase + OFF_QPART + k * 512 + lane * 16),
                         "r"(B[k].x), "r"(B[k].y), "r"(B[k].z), "r"(B[k].w) : "memory");
        mbar_arrive(bar0 + B_T * 8);
    } else {
        mbar_wait(bar0 + B_T * 8);
#pragma unroll
        for (int k = 0; k < 4; k++) A[k] = lds128(sbase + OFF_QPART + k * 512 + lane * 16);
    }
    uint32_t tag = lds32(sbase + OFF_GATE + 8);
    if (lane < 6) mbar_wait(bar0 + (B_FULL + 24 + lane) * 8);
    __syncwarp();
#pragma unroll
    for (int k = 0; k < 4; k++) B[k] = ld_relaxed4(box + k * 32);
    {
        const long long t0 = clock64();
        while (clock64() - t0 < PGAP) {}
    }
    uint4 V[4];
#pragma unroll
    for (int k = 0; k < 4; k++) V[k] = make_uint4(0, 0, 0, 0);
    while (true) {
#pragma unroll
        for (int k = 0; k < 4; k++) accept4(V[k], A[k], tag, pend, k);
        if (!__any_sync(0xffffffffu, pend)) break;
#pragma unroll
        for (int k = 0; k < 4; k++) ld_relaxed4_if(A[k], box + k * 32, pend & (1u << k));
        tag = lds32v(sbase + OFF_GATE + 8);
#pragma unroll
        for (int k = 0; k < 4; k++) accept4(V[k], B[k], tag, pend, k);
        if (!__any_sync(0xffffffffu, pend)) break;
#pragma unroll
        for (int k = 0; k < 4; k++) ld_relaxed4_if(B[k], box + k * 32, pend & (1u << k));
        tag = lds32v(sbase + OFF_GATE + 8);
        if (++n > SPIN_LIMIT) break;
    }
    float s0 = 0.f, s1 = 0.f, s2 = 0.f, s3 = 0.f;
#pragma unroll
    for (int k = 0; k < 4; k++) {
        const uint4 v = V[k];
        s0 += __uint_as_float(v.x); s1 += __uint_as_float(v.y);
        s2 += __uint_as_float(v.z); s3 += __uint_as_float(v.w);
    }
#pragma unroll
    for (int o = 2; o < 32; o <<= 1) {
        s0 += __shfl_xor_sync(0xffffffffu, s0, o); s1 += __shfl_xor_sync(0xffffffffu, s1, o);
        s2 += __shfl_xor_sync(0xffffffffu, s2, o); s3 += __shfl_xor_sync(0xffffffffu, s3, o);
    }
    if (hw) {
        if (lane < 2) asm volatile("st.shared.v4.f32 [%0], {%1,%2,%3,%4};" ::"r"(sbase + OFF_FIN + lane * 16), "f"(s0), "f"(s1), "f"(s2), "f"(s3) : "memory");
        asm volatile("bar.arrive 4, 64;" ::: "memory");
    } else {
        bar_sync(4, 64);
        if (lane < 2) {
            const float4 u = lds128f(sbase + OFF_FIN + lane * 16);
            *reinterpret_cast<uint2*>(out + b * 8 + lane * 4) = make_uint2(pack_bf2(s0 + u.x, s1 + u.y), pack_bf2(s2 + u.z, s3 + u.w));
        }
    }
}

__global__ void __cluster_dims__(4, 1, 1) __launch_bounds__(NTHREADS, 2)
fused_decode_kernel(const __grid_constant__ CUtensorMap map_wq, const __grid_constant__ CUtensorMap map_wg,
                    const __grid_constant__ CUtensorMap map_wu, const __grid_constant__ CUtensorMap map_v,
                    const __grid_constant__ CUtensorMap map_wo, const __grid_constant__ CUtensorMap map_wd,
                    const __nv_bfloat16* __restrict__ x, const __nv_bfloat16* __restrict__ kc,
                    const __nv_bfloat16* __restrict__ gate_w, __nv_bfloat16* __restrict__ out) {
    extern __shared__ __align__(1024) unsigned char smem[];
    const uint32_t sbase = smem_u32(smem);
    const int tid = threadIdx.x, warp = tid >> 5, lane = tid & 31;
    const int b = blockIdx.x, h = b >> 2, r = b & 3;
    const float LOG2E = 1.4426950408889634f;
    const uint32_t bar0 = sbase + OFF_BAR;
#define BAR(i) (bar0 + (i) * 8)

    if (warp == 10) {
        if (lane == 0) {
#pragma unroll
            for (int i = 0; i < DEPTH; i++) mbar_init(BAR(B_FULL + i), 1);
            *reinterpret_cast<volatile uint32_t*>(smem + OFF_GATE + 12) = 0u;
        }
        asm volatile("fence.mbarrier_init.release.cluster;" ::: "memory");
        asm volatile("fence.proxy.async.shared::cta;" ::: "memory");
        __syncwarp();
        asm volatile("barrier.cluster.arrive.relaxed;" ::: "memory");
        const uint32_t dst = sbase + (lane & 7) * SLOT, fb = BAR(B_FULL + (lane < NSTAGE ? lane : 0));
        const size_t key = (size_t)h * SK + (SK - WIN) + ((lane & 7) * 4 + r) * 32;
        auto issue = [&]() {
            if (lane < 5) {
                mbar_expect(fb, 12288);
                tensor_g2s(dst, &map_wq, h * DHEAD, r * 160 + lane * 32, fb);
            } else if (lane < 8) {
                const int row = r * 160 + (lane - 5) * 64;
                if (lane < 7) {
                    mbar_expect(fb, 12288);
                    tensor_g2s(dst, &map_wg, h * 48, row, fb);
                    tensor_g2s(dst + 3072, &map_wg, h * 48, row + 32, fb);
                    tensor_g2s(dst + 6144, &map_wu, h * 48, row, fb);
                    tensor_g2s(dst + 9216, &map_wu, h * 48, row + 32, fb);
                } else {
                    mbar_expect(fb, 6144);
                    tensor_g2s(dst, &map_wg, h * 48, row, fb);
                    tensor_g2s(dst + 3072, &map_wu, h * 48, row, fb);
                }
            } else if (lane < 16) {
                mbar_expect(fb, 12288);
                bulk_g2s(dst, kc + key * DHEAD, 12288, fb);
            } else if (lane < 24) {
                mbar_expect(fb, 12288);
                tensor3_g2s(dst, &map_v, (int)key, 0, fb);
            } else if (lane == 24) {
                mbar_expect(fb, 15360);
#pragma unroll
                for (int t = 0; t < 5; t++)
                    tensor3_g2s(t < 4 ? dst + t * 3072 : sbase + OFF_WDX, &map_wd, h * 48 + r * 12, t * 2, fb);
            } else {
                mbar_expect(fb, 12288);
                tensor3_g2s(dst, &map_wo, h * DHEAD + r * 48, (lane - 25) * 2, fb);
            }
        };
#pragma unroll 1
        for (int i = 0; i < DEPTH; i++) { if (lane == i) issue(); __syncwarp(); }
        asm volatile("barrier.cluster.wait.acquire;" ::: "memory");
        int nxt = DEPTH;
        uint32_t n = 0;
        while (nxt < NSTAGE) {
            const bool f = lane < nxt && mbar_test(fb);
            const bool e = lane < NEMPTY && mbar_test(BAR(B_EMPTY + (lane < NEMPTY ? lane : 0)));
            const uint32_t fm = __ballot_sync(0xffffffffu, f), em = __ballot_sync(0xffffffffu, e);
            const int c = __popc(fm), dep = DEPTH + (int)lds32(sbase + OFF_GATE + 12);
            while (nxt < NSTAGE && nxt < c + (nxt >= SWITCH ? DEND : dep) && (nxt < 8 || ((em >> (nxt - 8)) & 1u))) {
                if (lane == nxt) {
                    issue();
                }
                __syncwarp();
                nxt++;
            }
            if (++n > SPIN_LIMIT) break;
        }
        if (b < NRED) {
            final_reduce(b, 1, lane, sbase, out);
            if (lane == 0) TSTAMP(8);
        }
        return;
    }

    if (lane == 0) {
        const int i0 = DEPTH + (warp == 11 ? 10 : warp) * NINIT;
#pragma unroll
        for (int k = 0; k < NINIT; k++) {
            const int i = i0 + k;
            if (i < NBAR) {
                int cnt = 1;
                if (i >= B_EMPTY && i < B_EMPTY + 8) cnt = i < B_EMPTY + 5 ? 6 : 3;
                if (i >= B_EMPTY + 16 && i < B_EMPTY + NEMPTY) cnt = 4;
                if (i == B_Q2 || i == B_H || i == B_T) cnt = 32;
                if (i == B_GU) cnt = 2;
                if (i == B_P) cnt = 8;
                mbar_init(BAR(i), cnt);
                if (i == B_Q)  mbar_expect(BAR(i), 4 * 768);
                if (i == B_GU) mbar_expect(BAR(i), 4 * 96);
                if (i == B_ML) mbar_expect(BAR(i), 32 * 8);
                if (i == B_O)  mbar_expect(BAR(i), 4 * 192);
            }
        }
        asm volatile("fence.mbarrier_init.release.cluster;" ::: "memory");
        asm volatile("fence.proxy.async.shared::cta;" ::: "memory");
    }
    __syncwarp();
    asm volatile("barrier.cluster.arrive.relaxed;" ::: "memory");

    if (warp == 11) {
        __nv_bfloat16* hb = reinterpret_cast<__nv_bfloat16*>(smem + OFF_HB);
        const uint32_t epoch = ld_relaxed(&g_epoch), tag = ~epoch & 1u;
        uint32_t smid;
        asm volatile("mov.u32 %0, %smid;" : "=r"(smid));
        uint32_t* smcnt = g_smcnt + (smid & 255u);
        uint32_t old = 0;
        if (lane == 0) old = atomicAdd(smcnt, 1u);
        __syncwarp();
        asm volatile("barrier.cluster.wait.acquire;" ::: "memory");
        if (lane == 0 && (old >= 1u || ld_relaxed(smcnt + (old >> 31)) >= 2u))
            *reinterpret_cast<volatile uint32_t*>(smem + OFF_GATE + 12) = DEXTRA;
        __syncwarp();
        mbar_wait(BAR(B_Q));
#pragma unroll
        for (int k = 0; k < 2; k++) {
            const int j = lane + k * 32;
            if (j < 48) {
                const float4 a0 = lds128f(sbase + OFF_QPART + j * 16), a1 = lds128f(sbase + OFF_QPART + 768 + j * 16);
                const float4 a2 = lds128f(sbase + OFF_QPART + 1536 + j * 16), a3 = lds128f(sbase + OFF_QPART + 2304 + j * 16);
                *reinterpret_cast<uint2*>(smem + OFF_QS + j * 8) =
                    make_uint2(pack_bf2((a0.x + a1.x) + (a2.x + a3.x), (a0.y + a1.y) + (a2.y + a3.y)),
                               pack_bf2((a0.z + a1.z) + (a2.z + a3.z), (a0.w + a1.w) + (a2.w + a3.w)));
            }
        }
        mbar_arrive(BAR(B_Q2));
        if (lane == 0) TSTAMP(2);
        mbar_wait(BAR(B_GU));
        if (lane < 12) {
            const float* gp = reinterpret_cast<const float*>(smem + OFF_GUP);
            const float gv = bfr((gp[lane] + gp[24 + lane]) + (gp[48 + lane] + gp[72 + lane]));
            const float uv = bfr((gp[12 + lane] + gp[36 + lane]) + (gp[60 + lane] + gp[84 + lane]));
            const float inner = 0.7978845608028654f * (gv + 0.044715f * gv * gv * gv);
            const float ge = bfr(0.5f * gv * (1.f + tanhf(inner)));
            hb[lane] = __float2bfloat16_rn(ge * uv);
        } else if (lane < 16) hb[lane] = __float2bfloat16_rn(0.f);
        else if (lane == 16) *reinterpret_cast<uint32_t*>(smem + OFF_GATE + 8) = tag;
        mbar_arrive(BAR(B_H));
        if (lane == 0) atomicSub(smcnt, 1u);
        if (b < NRED) {
            __syncwarp();
            final_reduce(b, 0, lane, sbase, out);
            if (b == 0 && lane == 0) st_relaxed(&g_epoch, epoch + 1u);
            if (lane == 0) TSTAMP(9);
        }
        return;
    }

    const float* xs = reinterpret_cast<const float*>(smem + OFF_XS);
    if (tid < 160) reinterpret_cast<float*>(smem + OFF_XS)[tid] = __bfloat162float(x[r * 160 + tid]);
    bar_sync(3, 320);
    asm volatile("barrier.cluster.wait.acquire;" ::: "memory");
    if (warp < 6) {
        const int c3 = warp % 3, hf = warp / 3, rs = lane >> 3;
        const uint32_t a = sbase + (hf * 16 + rs) * 384 + c3 * 128 + (lane & 7) * 16;
        float acc[8];
#pragma unroll
        for (int j = 0; j < 8; j++) acc[j] = 0.f;
#pragma unroll 1
        for (int s = 0; s < 5; s++) {
            float xv[4];
#pragma unroll
            for (int i = 0; i < 4; i++) xv[i] = xs[s * 32 + hf * 16 + rs + 4 * i];
            mbar_wait(BAR(B_FULL + s));
#pragma unroll
            for (int i = 0; i < 4; i++) fma8(acc, xv[i], lds128(a + s * SLOT + i * 1536));
            __syncwarp();
            if (lane == 0) mbar_arrive(BAR(B_EMPTY + s));
        }
#pragma unroll
        for (int j = 0; j < 8; j++) {
            acc[j] += __shfl_xor_sync(0xffffffffu, acc[j], 8);
            acc[j] += __shfl_xor_sync(0xffffffffu, acc[j], 16);
        }
        if (lane < 16) {
            float4* dst = reinterpret_cast<float4*>(smem + OFF_RED1 + hf * 768 + c3 * 256 + (lane & 7) * 32 + rs * 16);
            *dst = rs ? make_float4(acc[4], acc[5], acc[6], acc[7]) : make_float4(acc[0], acc[1], acc[2], acc[3]);
        }
        bar_sync(1, 192);
        const int dest = tid / 48, quad = tid % 48;
        const float4 u0 = lds128f(sbase + OFF_RED1 + quad * 16), u1 = lds128f(sbase + OFF_RED1 + 768 + quad * 16);
        st_async4(mapa(sbase + OFF_QPART + r * 768 + quad * 16, dest), u0.x + u1.x, u0.y + u1.y, u0.z + u1.z,
                  u0.w + u1.w, mapa(BAR(B_Q), dest));
        if (tid == 0) TSTAMP(1);
    } else if (warp < 9) {
        const int t = tid - 192, rg = t / 6;
        float ag[8], au[8];
#pragma unroll
        for (int j = 0; j < 8; j++) { ag[j] = 0.f; au[j] = 0.f; }
#pragma unroll
        for (int s = 0; s < 3; s++) {
            const uint32_t a = sbase + (5 + s) * SLOT + t * 16;
            mbar_wait(BAR(B_FULL + 5 + s));
#pragma unroll
            for (int i = 0; i < (s < 2 ? 4 : 2); i++) {
                const float xv = xs[s * 64 + rg + 16 * i];
                fma8(ag, xv, lds128(a + i * 1536));
                fma8(au, xv, lds128(a + (s < 2 ? 6144 : 3072) + i * 1536));
            }
            if (s < 2) {
                __syncwarp();
                if (lane == 0) mbar_arrive(BAR(B_EMPTY + 5 + s));
            }
        }
        float* red2 = reinterpret_cast<float*>(smem + 7 * SLOT + 6144);
        float4* dst = reinterpret_cast<float4*>(red2 + rg * 96 + (t % 6) * 8);
        dst[0] = make_float4(ag[0], ag[1], ag[2], ag[3]);   dst[1] = make_float4(ag[4], ag[5], ag[6], ag[7]);
        dst[12] = make_float4(au[0], au[1], au[2], au[3]);  dst[13] = make_float4(au[4], au[5], au[6], au[7]);
        bar_sync(2, 96);
        float s = 0.f;
#pragma unroll
        for (int i = 0; i < 16; i++) s += red2[i * 96 + t];
        const int c = t % 48, dest = c / 12;
        st_async1(mapa(sbase + OFF_GUP + (r * 24 + (t / 48) * 12 + c % 12) * 4, dest), s, mapa(BAR(B_GU), dest));
        asm volatile("fence.proxy.async.shared::cta;" ::: "memory");
        __syncwarp();
        if (lane == 0) mbar_arrive(BAR(B_EMPTY + 7));
    } else {
        float gs = 0.f;
        for (int c = lane; c < D_MODEL / 8; c += 32) {
            uint4 xv = *reinterpret_cast<const uint4*>(x + c * 8);
            uint4 gv = *reinterpret_cast<const uint4*>(gate_w + c * 8);
            gs += bfr(bf_lo(xv.x) * bf_lo(gv.x)) + bfr(bf_hi(xv.x) * bf_hi(gv.x));
            gs += bfr(bf_lo(xv.y) * bf_lo(gv.y)) + bfr(bf_hi(xv.y) * bf_hi(gv.y));
            gs += bfr(bf_lo(xv.z) * bf_lo(gv.z)) + bfr(bf_hi(xv.z) * bf_hi(gv.z));
            gs += bfr(bf_lo(xv.w) * bf_lo(gv.w)) + bfr(bf_hi(xv.w) * bf_hi(gv.w));
        }
#pragma unroll
        for (int o = 16; o > 0; o >>= 1) gs += __shfl_xor_sync(0xffffffffu, gs, o);
        const float gate = bfr(1.f / (1.f + __expf(-bfr(gs))));
        if (lane == 0) {
            *reinterpret_cast<float2*>(smem + OFF_GATE) = make_float2(gate, bfr(1.f - gate));
            mbar_arrive(BAR(B_GU));
        }
    }

    const int g = lane >> 2, t = lane & 3;
    if (warp < 8) {
        const int chunk = warp * 4 + r;
        const uint32_t slot = sbase + warp * SLOT;
        mbar_wait(BAR(B_Q2));
        uint32_t qf[6][4];
#pragma unroll
        for (int s = 0; s < 6; s++) {
            uint4 v = lds128(sbase + OFF_QS + (((s ^ (g & 1)) * 4 + t) * 16));
            qf[s][0] = v.x; qf[s][1] = v.y; qf[s][2] = v.z; qf[s][3] = v.w;
        }
        mbar_wait(BAR(B_FULL + 8 + warp));
        float c0[4] = {0.f, 0.f, 0.f, 0.f}, c1[4] = {0.f, 0.f, 0.f, 0.f};
        const uint32_t kb = slot + (16 * (g >> 2) + 2 * (g & 3)) * 384;
#pragma unroll
        for (int s = 0; s < 6; s++) {
            const uint32_t co = ((s ^ (g & 1)) * 4 + t) * 16;
            uint4 r0 = lds128(kb + co), r1 = lds128(kb + 384 + co), r2 = lds128(kb + 3072 + co), r3 = lds128(kb + 3456 + co);
            mma16816(c0, r0.x, r1.x, r0.y, r1.y, qf[s][0], qf[s][1]);
            mma16816(c1, r2.x, r3.x, r2.y, r3.y, qf[s][0], qf[s][1]);
            mma16816(c0, r0.z, r1.z, r0.w, r1.w, qf[s][2], qf[s][3]);
            mma16816(c1, r2.z, r3.z, r2.w, r3.w, qf[s][2], qf[s][3]);
        }
        __syncwarp();
        if (lane == 0) mbar_arrive(BAR(B_EMPTY + 8 + warp));
        const float scale = 0.07216878364870322f;
        float sc[4];
        sc[0] = (g & 1) ? c0[1] : c0[0];
        sc[1] = (g & 1) ? c0[3] : c0[2];
        sc[2] = (g & 1) ? c1[1] : c1[0];
        sc[3] = (g & 1) ? c1[3] : c1[2];
#pragma unroll
        for (int i = 0; i < 4; i++) sc[i] = bfr(bfr(sc[i]) * scale);
        float m = fmaxf(fmaxf(sc[0], sc[1]), fmaxf(sc[2], sc[3]));
#pragma unroll
        for (int o = 4; o < 32; o <<= 1) m = fmaxf(m, __shfl_xor_sync(0xffffffffu, m, o));
        float l = 0.f;
#pragma unroll
        for (int i = 0; i < 4; i++) l += exp2f((sc[i] - m) * LOG2E);
#pragma unroll
        for (int o = 4; o < 32; o <<= 1) l += __shfl_xor_sync(0xffffffffu, l, o);
        if (lane < 4) st_async2(mapa(sbase + OFF_ML + chunk * 8, lane), m, l, mapa(BAR(B_ML), lane));
        mbar_wait(BAR(B_ML));
        const float2 mlv = *reinterpret_cast<const float2*>(smem + OFF_ML + lane * 8);
        float M = mlv.x;
#pragma unroll
        for (int o = 16; o > 0; o >>= 1) M = fmaxf(M, __shfl_xor_sync(0xffffffffu, M, o));
        float L = exp2f((mlv.x - M) * LOG2E) * mlv.y;
#pragma unroll
        for (int o = 16; o > 0; o >>= 1) L += __shfl_xor_sync(0xffffffffu, L, o);
        const float inv = 1.f / L;
        if (t == 0) {
            float p[4];
#pragma unroll
            for (int i = 0; i < 4; i++) p[i] = exp2f((sc[i] - M) * LOG2E) * inv;
            *reinterpret_cast<uint2*>(smem + OFF_PS + (warp * 4 + (g & 3)) * 16 + (g >> 2) * 8) =
                make_uint2(pack_bf2(p[0], p[1]), pack_bf2(p[2], p[3]));
        }
        __syncwarp();
        if (lane == 0) mbar_arrive(BAR(B_P));
        if (tid == 0) TSTAMP(3);
    }
    if (warp < 4) {
        const uint32_t oaddr = mapa(sbase + OFF_OPART + r * 192, warp), obar = mapa(BAR(B_O), warp);
        const uint32_t vrow = sbase + ((lane & 7) + (lane >> 4) * 8) * 128;
        const uint32_t vsw = (lane & 7) ^ ((lane >> 3) & 1);
        uint32_t va[3];
#pragma unroll
        for (int j = 0; j < 3; j++) {
            const int mt = warp * 3 + j;
            va[j] = vrow + (mt >> 2) * 4096 + ((vsw ^ ((mt & 3) * 2)) << 4);
        }
        float acc[3][4];
#pragma unroll
        for (int j = 0; j < 3; j++) acc[j][0] = acc[j][1] = acc[j][2] = acc[j][3] = 0.f;
        mbar_wait(BAR(B_P));
#pragma unroll 1
        for (int s = 0; s < 8; s++) {
            const uint4 bp = lds128(sbase + OFF_PS + (s * 4 + t) * 16);
            mbar_wait(BAR(B_FULL + 16 + s));
            uint32_t a[6][4];
#pragma unroll
            for (int j = 0; j < 3; j++) {
                ldsm4t(a[j * 2], va[j] + s * SLOT);
                ldsm4t(a[j * 2 + 1], va[j] + s * SLOT + 2048);
            }
#pragma unroll
            for (int j = 0; j < 3; j++) mma16816(acc[j], a[j * 2][0], a[j * 2][1], a[j * 2][2], a[j * 2][3], bp.x, bp.y);
#pragma unroll
            for (int j = 0; j < 3; j++) mma16816(acc[j], a[j * 2 + 1][0], a[j * 2 + 1][1], a[j * 2 + 1][2], a[j * 2 + 1][3], bp.z, bp.w);
            __syncwarp();
            if (lane == 0 && s < 6) mbar_arrive(BAR(B_EMPTY + 16 + s));
        }
        if (t == 0) {
            st_async4(oaddr + g * 16, acc[0][0], acc[0][2], acc[1][0], acc[1][2], obar);
            st_async2(oaddr + 128 + (g & 3) * 16 + (g >> 2) * 8, acc[2][0], acc[2][2], obar);
        }
        if (tid == 0) TSTAMP(10);
    }
    {
        const int lk = lane & 7, lh = lane >> 4, lc = (lane >> 3) & 1;
        const int lro = (lk >> 1) + (lk & 1) * 4 + lh * 8;
        const int lrd = lk + lh * 8;
        const uint32_t wob = sbase + (1 + (warp >> 1)) * SLOT + (warp & 1) * 6144 + lro * 128;
        const uint32_t wdb = (warp < 8 ? sbase + warp * 1536 : sbase + OFF_WDX + (warp - 8) * 1536) + (lrd < 12 ? lrd : lrd - 4) * 128;
        const uint32_t swo = (lro & 7) ^ lc, swd = ((wdb >> 7) & 7) ^ lc;
        uint32_t* dst = reinterpret_cast<uint32_t*>(g_ex3) + ((size_t)(warp * 8 + t * 2) * NCTA + b) * 8 + g;
        float acc[4][4];
        mbar_wait(BAR(B_H));
        const float4 gt = lds128f(sbase + OFF_GATE);
        {
            const uint32_t v0 = lds32(sbase + OFF_HB + t * 4), v1 = lds32(sbase + OFF_HB + 16 + t * 4);
            const uint32_t h0 = (g & 1) ? v0 : 0u, h1 = (g & 1) ? v1 : 0u;
            mbar_wait(BAR(B_FULL + 24));
#pragma unroll
            for (int mt = 0; mt < 4; mt++) {
                acc[mt][0] = acc[mt][1] = acc[mt][2] = acc[mt][3] = 0.f;
                uint32_t a[4];
                ldsm4t(a, wdb + ((swd ^ (mt * 2)) << 4));
                mma16816(acc[mt], a[0], a[1], a[2], a[3], h0, h1);
            }
        }
        mbar_wait(BAR(B_O));
        if (tid == 0) TSTAMP(4);
        uint32_t bc[3][2];
        {
            float4 f[3];
#pragma unroll
            for (int i = 0; i < 3; i++) {
                const uint32_t a = sbase + OFF_OPART + i * 64 + t * 16;
                const float4 a0 = lds128f(a), a1 = lds128f(a + 192), a2 = lds128f(a + 384), a3 = lds128f(a + 576);
                f[i] = make_float4((a0.x + a1.x) + (a2.x + a3.x), (a0.y + a1.y) + (a2.y + a3.y),
                                   (a0.z + a1.z) + (a2.z + a3.z), (a0.w + a1.w) + (a2.w + a3.w));
            }
            const bool on = (g & 1) == 0;
            bc[0][0] = on ? pack_bf2(f[0].x, f[1].x) : 0u; bc[0][1] = on ? pack_bf2(f[0].y, f[1].y) : 0u;
            bc[1][0] = on ? pack_bf2(f[0].z, f[1].z) : 0u; bc[1][1] = on ? pack_bf2(f[0].w, f[1].w) : 0u;
            bc[2][0] = on ? pack_bf2(f[2].x, f[2].z) : 0u; bc[2][1] = on ? pack_bf2(f[2].y, f[2].w) : 0u;
        }
        mbar_wait(BAR(B_FULL + 25 + (warp >> 1)));
#pragma unroll
        for (int ks = 0; ks < 3; ks++) {
#pragma unroll
            for (int mt = 0; mt < 4; mt++) {
                uint32_t a[4];
                ldsm4t(a, wob + ks * 2048 + ((swo ^ (mt * 2)) << 4));
                mma16816(acc[mt], a[0], a[1], a[2], a[3], bc[ks][0], bc[ks][1]);
            }
        }
        float r0 = 0.f, r1 = 0.f;
#pragma unroll
        for (int mt = 0; mt < 4; mt++)
            if (t == mt) { r0 = gt.x * acc[mt][0] + gt.y * acc[mt][1]; r1 = gt.x * acc[mt][2] + gt.y * acc[mt][3]; }
        const uint32_t tag = __float_as_uint(gt.z);
        st_relaxed(dst, (__float_as_uint(r0) & ~1u) | tag);
        st_relaxed(dst + NCTA * 8, (__float_as_uint(r1) & ~1u) | tag);
        if (tid == 0) TSTAMP(6);
    }
#undef BAR
}

typedef CUresult (*EncodeTiledFn)(CUtensorMap*, CUtensorMapDataType, cuuint32_t, void*, const cuuint64_t*, const cuuint64_t*,
                                  const cuuint32_t*, const cuuint32_t*, CUtensorMapInterleave, CUtensorMapSwizzle,
                                  CUtensorMapL2promotion, CUtensorMapFloatOOBfill);

void make_map(EncodeTiledFn fn, CUtensorMap* m, const void* ptr, uint64_t cols, uint64_t rows, uint32_t box_c, uint32_t box_r) {
    cuuint64_t dims[2] = {cols, rows};
    cuuint64_t strides[1] = {cols * 2};
    cuuint32_t box[2] = {box_c, box_r};
    cuuint32_t es[2] = {1, 1};
    fn(m, CU_TENSOR_MAP_DATA_TYPE_BFLOAT16, 2, const_cast<void*>(ptr), dims, strides, box, es, CU_TENSOR_MAP_INTERLEAVE_NONE,
       CU_TENSOR_MAP_SWIZZLE_NONE, CU_TENSOR_MAP_L2_PROMOTION_NONE, CU_TENSOR_MAP_FLOAT_OOB_FILL_NONE);
}

void make_map3(EncodeTiledFn fn, CUtensorMap* m, const void* ptr, uint64_t cols, uint64_t rows, uint32_t box_r, uint32_t box_b) {
    cuuint64_t dims[3] = {64, rows, cols / 64};
    cuuint64_t strides[2] = {cols * 2, 128};
    cuuint32_t box[3] = {64, box_r, box_b};
    cuuint32_t es[3] = {1, 1, 1};
    fn(m, CU_TENSOR_MAP_DATA_TYPE_BFLOAT16, 3, const_cast<void*>(ptr), dims, strides, box, es, CU_TENSOR_MAP_INTERLEAVE_NONE,
       CU_TENSOR_MAP_SWIZZLE_128B, CU_TENSOR_MAP_L2_PROMOTION_NONE, CU_TENSOR_MAP_FLOAT_OOB_FILL_NONE);
}

}

extern "C" void kernel_launch(void* const* d_in, const int* in_sizes, int n_in, void* d_out, int out_size) {
    (void)in_sizes; (void)n_in; (void)out_size;
    static EncodeTiledFn encode = nullptr;
    if (!encode) {
        cudaFuncSetAttribute(fused_decode_kernel, cudaFuncAttributeMaxDynamicSharedMemorySize, SMEM_BYTES);
        void* fn = nullptr;
        cudaDriverEntryPointQueryResult qr;
        cudaGetDriverEntryPoint("cuTensorMapEncodeTiled", &fn, cudaEnableDefault, &qr);
        encode = (EncodeTiledFn)fn;
    }
    CUtensorMap mq, mg, mu, mv, mo, md;
    make_map(encode, &mq, d_in[3], NHEAD * DHEAD, D_MODEL, DHEAD, 32);
    make_map(encode, &mg, d_in[6], DFF, D_MODEL, 48, 32);
    make_map(encode, &mu, d_in[7], DFF, D_MODEL, 48, 32);
    make_map3(encode, &mv, d_in[2], DHEAD, (uint64_t)NHEAD * SK, 32, 3);
    make_map3(encode, &mo, d_in[4], D_MODEL, NHEAD * DHEAD, 48, 2);
    make_map3(encode, &md, d_in[8], D_MODEL, DFF, 12, 2);
    const __nv_bfloat16* x  = (const __nv_bfloat16*)d_in[0];
    const __nv_bfloat16* kc = (const __nv_bfloat16*)d_in[1];
    const __nv_bfloat16* gw = (const __nv_bfloat16*)d_in[9];
    fused_decode_kernel<<<NCTA, NTHREADS, SMEM_BYTES>>>(mq, mg, mu, mv, mo, md, x, kc, gw, (__nv_bfloat16*)d_out);
}
```

```cpp
#include <cuda_runtime.h>
#include <cuda.h>
#include <cuda_bf16.h>
#include <stdint.h>

#define DEPTH 4
#define DMIN 3
#define DMAX 6
#define WDMIN 3
#define WDELAY 350
#define PI0 1600
#define PTS 490
#define TOUCH 20
#define PSTART 6

#define PBACK 0
#define PWAIT 0
#define WDPROMO 0
#define GUPROMO 0
#define WDPF 0
#define TUNE_PARAM
#define TUNE_ARG

namespace {

constexpr int D_MODEL = 640;
constexpr int NHEAD   = 32;
constexpr int DHEAD   = 192;
constexpr int SK      = 4096;
constexpr int WIN     = 1024;
constexpr int DFF     = 1536;

constexpr int NCTA     = 128;
constexpr int NTHREADS = 384;

constexpr int SLOT      = 12288;
constexpr int OFF_QPART = 8 * SLOT;
constexpr int OFF_RED1  = OFF_QPART + 3072;
constexpr int OFF_OPART = OFF_RED1 + 1536;
constexpr int OFF_PS    = OFF_OPART + 768;
constexpr int OFF_QS    = OFF_PS + 512;
constexpr int OFF_GUP   = OFF_QS + 384;
constexpr int OFF_ML    = OFF_GUP + 384;
constexpr int OFF_HB    = OFF_ML + 256;
constexpr int OFF_REC   = OFF_HB + 384;
constexpr int OFF_FIN   = OFF_REC + 256;
constexpr int OFF_GATE  = OFF_FIN + 128;
constexpr int OFF_XS    = OFF_GATE + 16;
constexpr int OFF_BAR   = OFF_XS + 640;
constexpr int NSTAGE = 31, NEMPTY = 23;
constexpr int B_FULL = 0, B_EMPTY = 31, B_Q = 54, B_Q2 = 55, B_GU = 56, B_ML = 57, B_P = 58, B_O = 59, B_T = 60, B_W = 61, NBAR = 62;
constexpr int NINIT = (NBAR - DEPTH + 10) / 11;
constexpr int SMEM_BYTES = OFF_BAR + NBAR * 8;
static_assert(SMEM_BYTES <= 115712, "two CTAs must fit on one SM");

__device__ __align__(4096) uint4 g_box[80 * NCTA * 2];
__device__ __align__(1024) uint4 g_hid[NCTA * 4];
__device__ uint32_t g_epoch;

constexpr uint32_t SPIN_LIMIT = 1u << 22;

__device__ __forceinline__ uint32_t smem_u32(const void* p) { return (uint32_t)__cvta_generic_to_shared(p); }
__device__ __forceinline__ void mbar_init(uint32_t bar, int cnt) {
    asm volatile("mbarrier.init.shared::cta.b64 [%0], %1;" ::"r"(bar), "r"(cnt) : "memory");
}
__device__ __forceinline__ void mbar_expect(uint32_t bar, uint32_t bytes) {
    asm volatile("mbarrier.arrive.expect_tx.shared::cta.b64 _, [%0], %1;" ::"r"(bar), "r"(bytes) : "memory");
}
__device__ __forceinline__ void mbar_arrive(uint32_t bar) {
    asm volatile("mbarrier.arrive.shared::cta.b64 _, [%0];" ::"r"(bar) : "memory");
}
__device__ __forceinline__ bool mbar_try(uint32_t bar) {
    uint32_t ok;
    asm volatile("{\n .reg .pred p;\n mbarrier.try_wait.parity.shared::cta.b64 p, [%1], 0;\n selp.u32 %0, 1, 0, p;\n }"
                 : "=r"(ok) : "r"(bar) : "memory");
    return ok != 0;
}
__device__ __forceinline__ bool mbar_test(uint32_t bar) {
    uint32_t ok;
    asm volatile("{\n .reg .pred p;\n mbarrier.test_wait.parity.shared::cta.b64 p, [%1], 0;\n selp.u32 %0, 1, 0, p;\n }"
                 : "=r"(ok) : "r"(bar) : "memory");
    return ok != 0;
}
__device__ __forceinline__ void mbar_wait(uint32_t bar) {
    uint32_t n = 0;
    while (!mbar_try(bar)) { if (++n > SPIN_LIMIT) break; }
}
__device__ __forceinline__ uint32_t mapa(uint32_t addr, uint32_t rank) {
    uint32_t r;
    asm("mapa.shared::cluster.u32 %0, %1, %2;" : "=r"(r) : "r"(addr), "r"(rank));
    return r;
}
__device__ __forceinline__ void st_async4(uint32_t addr, float a, float b, float c, float d, uint32_t bar) {
    asm volatile("st.async.weak.shared::cluster.mbarrier::complete_tx::bytes.v4.f32 [%0], {%1,%2,%3,%4}, [%5];"
                 ::"r"(addr), "f"(a), "f"(b), "f"(c), "f"(d), "r"(bar) : "memory");
}
__device__ __forceinline__ void st_async2(uint32_t addr, float a, float b, uint32_t bar) {
    asm volatile("st.async.weak.shared::cluster.mbarrier::complete_tx::bytes.v2.f32 [%0], {%1,%2}, [%3];"
                 ::"r"(addr), "f"(a), "f"(b), "r"(bar) : "memory");
}
__device__ __forceinline__ void st_async1(uint32_t addr, float a, uint32_t bar) {
    asm volatile("st.async.weak.shared::cluster.mbarrier::complete_tx::bytes.f32 [%0], %1, [%2];"
                 ::"r"(addr), "f"(a), "r"(bar) : "memory");
}
__device__ __forceinline__ void bulk_g2s(uint32_t dst, const void* src, uint32_t bytes, uint32_t bar) {
    asm volatile("cp.async.bulk.shared::cluster.global.mbarrier::complete_tx::bytes [%0], [%1], %2, [%3];"
                 ::"r"(dst), "l"(src), "r"(bytes), "r"(bar) : "memory");
}
__device__ __forceinline__ void tensor_g2s(uint32_t dst, const CUtensorMap* map, int c0, int c1, uint32_t bar) {
    asm volatile("cp.async.bulk.tensor.2d.shared::cluster.global.mbarrier::complete_tx::bytes [%0], [%1, {%3, %4}], [%2];"
                 ::"r"(dst), "l"(map), "r"(bar), "r"(c0), "r"(c1) : "memory");
}
__device__ __forceinline__ void tensor3_g2s(uint32_t dst, const CUtensorMap* map, int c1, int c2, uint32_t bar) {
    asm volatile("cp.async.bulk.tensor.3d.shared::cluster.global.mbarrier::complete_tx::bytes [%0], [%1, {%3, %4, %5}], [%2];"
                 ::"r"(dst), "l"(map), "r"(bar), "r"(0), "r"(c1), "r"(c2) : "memory");
}
__device__ __forceinline__ void ldsm4t(uint32_t (&a)[4], uint32_t addr) {
    asm volatile("ldmatrix.sync.aligned.m8n8.x4.trans.shared.b16 {%0,%1,%2,%3}, [%4];"
                 : "=r"(a[0]), "=r"(a[1]), "=r"(a[2]), "=r"(a[3]) : "r"(addr));
}
__device__ __forceinline__ uint32_t lds32(uint32_t addr) {
    uint32_t v;
    asm volatile("ld.shared.u32 %0, [%1];" : "=r"(v) : "r"(addr));
    return v;
}
__device__ __forceinline__ void st_relaxed(uint32_t* p, uint32_t v) {
    asm volatile("st.relaxed.gpu.global.u32 [%0], %1;" ::"l"(p), "r"(v) : "memory");
}
__device__ __forceinline__ uint32_t ld_relaxed(const uint32_t* p) {
    uint32_t v;
    asm volatile("ld.relaxed.gpu.global.u32 %0, [%1];" : "=r"(v) : "l"(p) : "memory");
    return v;
}
__device__ __forceinline__ uint4 ld_relaxed4(const uint4* p) {
    uint4 v;
    asm volatile("ld.relaxed.gpu.global.v4.u32 {%0,%1,%2,%3}, [%4];"
                 : "=r"(v.x), "=r"(v.y), "=r"(v.z), "=r"(v.w) : "l"(p) : "memory");
    return v;
}
__device__ __forceinline__ void st_relaxed4(uint4* p, uint4 v) {
    asm volatile("st.relaxed.gpu.global.v4.u32 [%0], {%1,%2,%3,%4};" ::"l"(p), "r"(v.x), "r"(v.y), "r"(v.z), "r"(v.w) : "memory");
}
__device__ __forceinline__ void bar_sync(int id, int n) { asm volatile("bar.sync %0, %1;" ::"r"(id), "r"(n) : "memory"); }
__device__ __forceinline__ float bf_lo(uint32_t w) { return __uint_as_float(w << 16); }
__device__ __forceinline__ float bf_hi(uint32_t w) { return __uint_as_float(w & 0xffff0000u); }
__device__ __forceinline__ float bfr(float f) { return __bfloat162float(__float2bfloat16_rn(f)); }
__device__ __forceinline__ uint32_t pack_bf2(float lo, float hi) {
    __nv_bfloat162 t = __floats2bfloat162_rn(lo, hi);
    return *reinterpret_cast<uint32_t*>(&t);
}
__device__ __forceinline__ void mma16816(float (&c)[4], uint32_t a0, uint32_t a1, uint32_t a2, uint32_t a3,
                                         uint32_t b0, uint32_t b1) {
    asm volatile("mma.sync.aligned.m16n8k16.row.col.f32.bf16.bf16.f32 {%0,%1,%2,%3}, {%4,%5,%6,%7}, {%8,%9}, {%0,%1,%2,%3};"
                 : "+f"(c[0]), "+f"(c[1]), "+f"(c[2]), "+f"(c[3])
                 : "r"(a0), "r"(a1), "r"(a2), "r"(a3), "r"(b0), "r"(b1));
}
__device__ __forceinline__ uint4 lds128(uint32_t addr) {
    uint4 v;
    asm volatile("ld.shared.v4.u32 {%0,%1,%2,%3}, [%4];" : "=r"(v.x), "=r"(v.y), "=r"(v.z), "=r"(v.w) : "r"(addr));
    return v;
}
__device__ __forceinline__ float4 lds128f(uint32_t addr) {
    float4 v;
    asm volatile("ld.shared.v4.f32 {%0,%1,%2,%3}, [%4];" : "=f"(v.x), "=f"(v.y), "=f"(v.z), "=f"(v.w) : "r"(addr));
    return v;
}
__device__ __forceinline__ void fma8(float (&acc)[8], float xv, const uint4& w) {
    acc[0] = fmaf(xv, bf_lo(w.x), acc[0]); acc[1] = fmaf(xv, bf_hi(w.x), acc[1]);
    acc[2] = fmaf(xv, bf_lo(w.y), acc[2]); acc[3] = fmaf(xv, bf_hi(w.y), acc[3]);
    acc[4] = fmaf(xv, bf_lo(w.z), acc[4]); acc[5] = fmaf(xv, bf_hi(w.z), acc[5]);
    acc[6] = fmaf(xv, bf_lo(w.w), acc[6]); acc[7] = fmaf(xv, bf_hi(w.w), acc[7]);
}

#define TSTAMP(i) do {} while (0)

__device__ __forceinline__ void ld_relaxed4_if(uint4& v, const uint4* p, uint32_t cond) {
    asm volatile("{\n .reg .pred p;\n setp.ne.u32 p, %5, 0;\n @p ld.relaxed.gpu.global.v4.u32 {%0,%1,%2,%3}, [%4];\n}"
                 : "+r"(v.x), "+r"(v.y), "+r"(v.z), "+r"(v.w) : "l"(p), "r"(cond) : "memory");
}
__device__ __forceinline__ uint32_t timer_ns() {
    uint32_t t;
    asm volatile("mov.u32 %0, %globaltimer_lo;" : "=r"(t));
    return t;
}

__global__ void __cluster_dims__(8, 1, 1) __launch_bounds__(NTHREADS, 2)
fused_decode_kernel(const __grid_constant__ CUtensorMap map_wq, const __grid_constant__ CUtensorMap map_wg,
                    const __grid_constant__ CUtensorMap map_wu, const __grid_constant__ CUtensorMap map_v,
                    const __grid_constant__ CUtensorMap map_wo, const __grid_constant__ CUtensorMap map_wd,
                    const __nv_bfloat16* __restrict__ x, const __nv_bfloat16* __restrict__ kc,
                    const __nv_bfloat16* __restrict__ gate_w, const __nv_bfloat16* __restrict__ wd,
                    __nv_bfloat16* __restrict__ out TUNE_PARAM) {
    extern __shared__ __align__(1024) unsigned char smem[];
    const uint32_t sbase = smem_u32(smem);
    const int tid = threadIdx.x, warp = tid >> 5, lane = tid & 31;
    const int b = blockIdx.x, h = b >> 2, r = b & 3;
    const int cr = b & 7, rb = b & 4;
    const int oct = (b >> 3) * 5 + cr;
    const float LOG2E = 1.4426950408889634f;
    const uint32_t bar0 = sbase + OFF_BAR;
#define BAR(i) (bar0 + (i) * 8)

    if (warp == 10) {
        const uint32_t due = timer_ns() + PI0 + (lane - 4) * PTS - (lane > 7 ? PTS / 2 : 0) - (lane > 29 ? PTS * 3 / 8 : 0) +
                             (lane > 28 ? WDELAY : 0);
        if (lane == 0) {
#pragma unroll
            for (int i = 0; i < DEPTH; i++) mbar_init(BAR(B_FULL + i), 1);
        }
        asm volatile("fence.mbarrier_init.release.cluster;" ::: "memory");
        asm volatile("fence.proxy.async.shared::cta;" ::: "memory");
        __syncwarp();
        asm volatile("barrier.cluster.arrive.relaxed;" ::: "memory");
        const uint32_t dst = sbase + (lane & 7) * SLOT, fb = BAR(B_FULL + (lane < NSTAGE ? lane : 0));
        const size_t key = (size_t)h * SK + (SK - WIN) + ((lane & 7) * 4 + r) * 32;
        auto issue = [&]() {
            if (lane < 5) {
                mbar_expect(fb, 12288);
                tensor_g2s(dst, &map_wq, h * DHEAD, r * 160 + lane * 32, fb);
            } else if (lane < 8) {
                const int row = r * 160 + (lane - 5) * 64;
                if (lane < 7) {
                    mbar_expect(fb, 12288);
                    tensor_g2s(dst, &map_wg, h * 48, row, fb);
                    tensor_g2s(dst + 3072, &map_wg, h * 48, row + 32, fb);
                    tensor_g2s(dst + 6144, &map_wu, h * 48, row, fb);
                    tensor_g2s(dst + 9216, &map_wu, h * 48, row + 32, fb);
                } else {
                    mbar_expect(fb, 6144);
                    tensor_g2s(dst, &map_wg, h * 48, row, fb);
                    tensor_g2s(dst + 3072, &map_wu, h * 48, row, fb);
                }
            } else if (lane < 16) {
                mbar_expect(fb, 12288);
                bulk_g2s(dst, kc + key * DHEAD, 12288, fb);
            } else if (lane < 24) {
                mbar_expect(fb, 12288);
                tensor3_g2s(dst, &map_v, 0, (int)key, fb);
            } else if (lane < 29) {
                mbar_expect(fb, 12288);
                tensor3_g2s(dst, &map_wo, h * DHEAD + r * 48, (lane - 24) * 2, fb);
            } else {
                mbar_expect(fb, 7680);
                tensor_g2s(dst, &map_wd, (b >> 3) * 40, cr * 192 + (lane - 29) * 96, fb);
            }
        };
#pragma unroll 1
        for (int i = 0; i < DEPTH; i++) { if (lane == i) issue(); __syncwarp(); }
        asm volatile("barrier.cluster.wait.acquire;" ::: "memory");
        int nxt = DEPTH;
        uint32_t n = 0;
        bool f = false, e = lane >= NEMPTY;
        while (nxt < NSTAGE) {
            if (!f && lane < nxt) f = mbar_test(fb);
            if (!e && (unsigned)(lane + 8 - nxt) < 2u) e = mbar_test(BAR(B_EMPTY + lane));
            const uint32_t em = __ballot_sync(0xffffffffu, e);
            const uint32_t tm = __ballot_sync(0xffffffffu, (int)(timer_ns() - due) >= 0);
            const int c = __popc(__ballot_sync(0xffffffffu, f));
            while (nxt < NSTAGE && nxt < c + (((tm >> nxt) & 1u) ? DMAX : nxt > 28 ? WDMIN : DMIN) &&
                   (nxt < 8 || ((em >> (nxt - 8)) & 1u))) {
                if (lane == nxt) {
                    issue();
                }
                __syncwarp();
                nxt++;
            }
            if (++n > SPIN_LIMIT) break;
        }
        return;
    }

    if (lane == 0) {
        const int i0 = DEPTH + (warp == 11 ? 10 : warp) * NINIT;
#pragma unroll
        for (int k = 0; k < NINIT; k++) {
            const int i = i0 + k;
            if (i < NBAR) {
                int cnt = 1;
                if (i >= B_EMPTY && i < B_EMPTY + 8) cnt = i < B_EMPTY + 5 ? 6 : 3;
                if (i >= B_EMPTY + 16 && i < B_EMPTY + NEMPTY) cnt = 4;
                if (i == B_Q2 || i == B_T) cnt = 32;
                if (i == B_GU) cnt = 2;
                if (i == B_P) cnt = 8;
                if (i == B_W) cnt = 33;
                mbar_init(BAR(i), cnt);
                if (i == B_Q)  mbar_expect(BAR(i), 4 * 768);
                if (i == B_GU) mbar_expect(BAR(i), 4 * 96);
                if (i == B_ML) mbar_expect(BAR(i), 32 * 8);
                if (i == B_O)  mbar_expect(BAR(i), 4 * 192);
                if (i == B_W)  mbar_expect(BAR(i), 8 * 32);
            }
        }
        asm volatile("fence.mbarrier_init.release.cluster;" ::: "memory");
        asm volatile("fence.proxy.async.shared::cta;" ::: "memory");
    }
    __syncwarp();
    asm volatile("barrier.cluster.arrive.relaxed;" ::: "memory");

    if (warp == 11) {
        const uint32_t epoch = ld_relaxed(&g_epoch), tag16 = (epoch + 1u) & 0xffffu;
        asm volatile("barrier.cluster.wait.acquire;" ::: "memory");
        mbar_wait(BAR(B_Q));
#pragma unroll
        for (int k = 0; k < 2; k++) {
            const int j = lane + k * 32;
            if (j < 48) {
                const float4 a0 = lds128f(sbase + OFF_QPART + j * 16), a1 = lds128f(sbase + OFF_QPART + 768 + j * 16);
                const float4 a2 = lds128f(sbase + OFF_QPART + 1536 + j * 16), a3 = lds128f(sbase + OFF_QPART + 2304 + j * 16);
                *reinterpret_cast<uint2*>(smem + OFF_QS + j * 8) =
                    make_uint2(pack_bf2((a0.x + a1.x) + (a2.x + a3.x), (a0.y + a1.y) + (a2.y + a3.y)),
                               pack_bf2((a0.z + a1.z) + (a2.z + a3.z), (a0.w + a1.w) + (a2.w + a3.w)));
            }
        }
        mbar_arrive(BAR(B_Q2));
        if (lane == 0) TSTAMP(2);
        mbar_wait(BAR(B_GU));
        if (lane < 16) {
            const float* gp = reinterpret_cast<const float*>(smem + OFF_GUP);
            const int i = lane < 12 ? lane : 0;
            const float gv = bfr((gp[i] + gp[24 + i]) + (gp[48 + i] + gp[72 + i]));
            const float uv = bfr((gp[12 + i] + gp[36 + i]) + (gp[60 + i] + gp[84 + i]));
            const float inner = 0.7978845608028654f * (gv + 0.044715f * gv * gv * gv);
            const float ge = bfr(0.5f * gv * (1.f + tanhf(inner)));
            st_relaxed(reinterpret_cast<uint32_t*>(g_hid) + b * 16 + lane, __float_as_uint(bfr(ge * uv)) | tag16);
        } else if (lane == 16) *reinterpret_cast<uint32_t*>(smem + OFF_GATE + 8) = tag16 & 1u;
        const float2 gt = *reinterpret_cast<const float2*>(smem + OFF_GATE);
        mbar_wait(BAR(B_FULL + TOUCH));
        {
            const uint4* hp = g_hid + cr * 64 + lane;
            uint4* ib = g_box + ((size_t)(lane >> 1) * NCTA + b) * 2 + (lane & 1);
            uint4 v[2];
            v[0] = ld_relaxed4(hp);
            v[1] = ld_relaxed4(hp + 32);
#pragma unroll
            for (int k = 0; k < 5; k++) st_relaxed4(ib + k * 16 * NCTA * 2, make_uint4(0u, 1u, 0u, 1u));
#pragma unroll
            for (int k = 0; k < 2; k++) {
                for (uint32_t n = 0; n < SPIN_LIMIT; n++) {
                    if (!(((v[k].x ^ tag16) | (v[k].y ^ tag16) | (v[k].z ^ tag16) | (v[k].w ^ tag16)) & 0xffffu)) break;
                    v[k] = ld_relaxed4(hp + k * 32);
                }
                if ((lane & 3) != 3) {
                    const int kk = (k * 8 + (lane >> 2)) * 12 + (lane & 3) * 4;
                    const uint32_t a = sbase + OFF_HB + (kk >> 5) * 64 + ((kk & 7) >> 1) * 16 + ((kk >> 3) & 3) * 4;
                    asm volatile("st.shared.u32 [%0], %1;" ::"r"(a), "r"(__byte_perm(v[k].x, v[k].y, 0x7632)) : "memory");
                    asm volatile("st.shared.u32 [%0], %1;" ::"r"(a + 16), "r"(__byte_perm(v[k].z, v[k].w, 0x7632)) : "memory");
                }
            }
            mbar_arrive(BAR(B_T));
        }
        if (cr < 5) {
            mbar_wait(BAR(B_W));
            if (lane < 8) {
                const float4 u = lds128f(sbase + OFF_FIN + lane * 16);
                const float* rp = reinterpret_cast<const float*>(smem + OFF_REC) + lane;
                const float av = bfr((u.x + u.y) + (u.z + u.w));
                const float bv = bfr(((rp[0] + rp[8]) + (rp[16] + rp[24])) + ((rp[32] + rp[40]) + (rp[48] + rp[56])));
                out[oct * 8 + lane] = __float2bfloat16_rn(bfr(gt.x * av) + bfr(gt.y * bv));
            }
            if (b == 0 && lane == 0) st_relaxed(&g_epoch, epoch + 1u);
            if (lane == 0) TSTAMP(9);
        }
        return;
    }

    const float* xs = reinterpret_cast<const float*>(smem + OFF_XS);
    if (tid < 160) reinterpret_cast<float*>(smem + OFF_XS)[tid] = __bfloat162float(x[r * 160 + tid]);
    bar_sync(3, 320);
    asm volatile("barrier.cluster.wait.acquire;" ::: "memory");
    if (warp < 6) {
        const int c3 = warp % 3, hf = warp / 3, rs = lane >> 3;
        const uint32_t a = sbase + (hf * 16 + rs) * 384 + c3 * 128 + (lane & 7) * 16;
        float acc[8];
#pragma unroll
        for (int j = 0; j < 8; j++) acc[j] = 0.f;
#pragma unroll 1
        for (int s = 0; s < 5; s++) {
            float xv[4];
#pragma unroll
            for (int i = 0; i < 4; i++) xv[i] = xs[s * 32 + hf * 16 + rs + 4 * i];
            mbar_wait(BAR(B_FULL + s));
#pragma unroll
            for (int i = 0; i < 4; i++) fma8(acc, xv[i], lds128(a + s * SLOT + i * 1536));
            __syncwarp();
            if (lane == 0) mbar_arrive(BAR(B_EMPTY + s));
        }
#pragma unroll
        for (int j = 0; j < 8; j++) {
            acc[j] += __shfl_xor_sync(0xffffffffu, acc[j], 8);
            acc[j] += __shfl_xor_sync(0xffffffffu, acc[j], 16);
        }
        if (lane < 16) {
            float4* dst = reinterpret_cast<float4*>(smem + OFF_RED1 + hf * 768 + c3 * 256 + (lane & 7) * 32 + rs * 16);
            *dst = rs ? make_float4(acc[4], acc[5], acc[6], acc[7]) : make_float4(acc[0], acc[1], acc[2], acc[3]);
        }
        bar_sync(1, 192);
        const int dest = rb + tid / 48, quad = tid % 48;
        const float4 u0 = lds128f(sbase + OFF_RED1 + quad * 16), u1 = lds128f(sbase + OFF_RED1 + 768 + quad * 16);
        st_async4(mapa(sbase + OFF_QPART + r * 768 + quad * 16, dest), u0.x + u1.x, u0.y + u1.y, u0.z + u1.z,
                  u0.w + u1.w, mapa(BAR(B_Q), dest));
        if (tid == 0) TSTAMP(1);
    } else if (warp < 9) {
        const int t = tid - 192, rg = t / 6;
        float ag[8], au[8];
#pragma unroll
        for (int j = 0; j < 8; j++) { ag[j] = 0.f; au[j] = 0.f; }
#pragma unroll
        for (int s = 0; s < 3; s++) {
            const uint32_t a = sbase + (5 + s) * SLOT + t * 16;
            mbar_wait(BAR(B_FULL + 5 + s));
#pragma unroll
            for (int i = 0; i < (s < 2 ? 4 : 2); i++) {
                const float xv = xs[s * 64 + rg + 16 * i];
                fma8(ag, xv, lds128(a + i * 1536));
                fma8(au, xv, lds128(a + (s < 2 ? 6144 : 3072) + i * 1536));
            }
            if (s < 2) {
                __syncwarp();
                if (lane == 0) mbar_arrive(BAR(B_EMPTY + 5 + s));
            }
        }
        float* red2 = reinterpret_cast<float*>(smem + 7 * SLOT + 6144);
        float4* dst = reinterpret_cast<float4*>(red2 + rg * 96 + (t % 6) * 8);
        dst[0] = make_float4(ag[0], ag[1], ag[2], ag[3]);   dst[1] = make_float4(ag[4], ag[5], ag[6], ag[7]);
        dst[12] = make_float4(au[0], au[1], au[2], au[3]);  dst[13] = make_float4(au[4], au[5], au[6], au[7]);
        bar_sync(2, 96);
        float s = 0.f;
#pragma unroll
        for (int i = 0; i < 16; i++) s += red2[i * 96 + t];
        const int c = t % 48, dest = rb + c / 12;
        st_async1(mapa(sbase + OFF_GUP + (r * 24 + (t / 48) * 12 + c % 12) * 4, dest), s, mapa(BAR(B_GU), dest));
        asm volatile("fence.proxy.async.shared::cta;" ::: "memory");
        __syncwarp();
        if (lane == 0) mbar_arrive(BAR(B_EMPTY + 7));
    } else {
        float gs = 0.f;
        for (int c = lane; c < D_MODEL / 8; c += 32) {
            uint4 xv = *reinterpret_cast<const uint4*>(x + c * 8);
            uint4 gv = *reinterpret_cast<const uint4*>(gate_w + c * 8);
            gs += bfr(bf_lo(xv.x) * bf_lo(gv.x)) + bfr(bf_hi(xv.x) * bf_hi(gv.x));
            gs += bfr(bf_lo(xv.y) * bf_lo(gv.y)) + bfr(bf_hi(xv.y) * bf_hi(gv.y));
            gs += bfr(bf_lo(xv.z) * bf_lo(gv.z)) + bfr(bf_hi(xv.z) * bf_hi(gv.z));
            gs += bfr(bf_lo(xv.w) * bf_lo(gv.w)) + bfr(bf_hi(xv.w) * bf_hi(gv.w));
        }
#pragma unroll
        for (int o = 16; o > 0; o >>= 1) gs += __shfl_xor_sync(0xffffffffu, gs, o);
        const float gate = bfr(1.f / (1.f + __expf(-bfr(gs))));
        if (lane == 0) {
            *reinterpret_cast<float2*>(smem + OFF_GATE) = make_float2(gate, bfr(1.f - gate));
            mbar_arrive(BAR(B_GU));
        }
    }

    const int g = lane >> 2, t = lane & 3;
    if (warp < 8) {
        const int chunk = warp * 4 + r;
        const uint32_t slot = sbase + warp * SLOT;
        mbar_wait(BAR(B_Q2));
        uint32_t qf[6][4];
#pragma unroll
        for (int s = 0; s < 6; s++) {
            uint4 v = lds128(sbase + OFF_QS + (((s ^ (g & 1)) * 4 + t) * 16));
            qf[s][0] = v.x; qf[s][1] = v.y; qf[s][2] = v.z; qf[s][3] = v.w;
        }
        mbar_wait(BAR(B_FULL + 8 + warp));
        float c0[4] = {0.f, 0.f, 0.f, 0.f}, c1[4] = {0.f, 0.f, 0.f, 0.f};
        const uint32_t kb = slot + (16 * (g >> 2) + 2 * (g & 3)) * 384;
#pragma unroll
        for (int s = 0; s < 6; s++) {
            const uint32_t co = ((s ^ (g & 1)) * 4 + t) * 16;
            uint4 r0 = lds128(kb + co), r1 = lds128(kb + 384 + co), r2 = lds128(kb + 3072 + co), r3 = lds128(kb + 3456 + co);
            mma16816(c0, r0.x, r1.x, r0.y, r1.y, qf[s][0], qf[s][1]);
            mma16816(c1, r2.x, r3.x, r2.y, r3.y, qf[s][0], qf[s][1]);
            mma16816(c0, r0.z, r1.z, r0.w, r1.w, qf[s][2], qf[s][3]);
            mma16816(c1, r2.z, r3.z, r2.w, r3.w, qf[s][2], qf[s][3]);
        }
        __syncwarp();
        if (lane == 0) mbar_arrive(BAR(B_EMPTY + 8 + warp));
        const float scale = 0.07216878364870322f;
        float sc[4];
        sc[0] = (g & 1) ? c0[1] : c0[0];
        sc[1] = (g & 1) ? c0[3] : c0[2];
        sc[2] = (g & 1) ? c1[1] : c1[0];
        sc[3] = (g & 1) ? c1[3] : c1[2];
#pragma unroll
        for (int i = 0; i < 4; i++) sc[i] = bfr(bfr(sc[i]) * scale);
        float m = fmaxf(fmaxf(sc[0], sc[1]), fmaxf(sc[2], sc[3]));
#pragma unroll
        for (int o = 4; o < 32; o <<= 1) m = fmaxf(m, __shfl_xor_sync(0xffffffffu, m, o));
        float l = 0.f;
#pragma unroll
        for (int i = 0; i < 4; i++) l += exp2f((sc[i] - m) * LOG2E);
#pragma unroll
        for (int o = 4; o < 32; o <<= 1) l += __shfl_xor_sync(0xffffffffu, l, o);
        if (lane < 4) st_async2(mapa(sbase + OFF_ML + chunk * 8, rb + lane), m, l, mapa(BAR(B_ML), rb + lane));
        mbar_wait(BAR(B_ML));
        const float2 mlv = *reinterpret_cast<const float2*>(smem + OFF_ML + lane * 8);
        float M = mlv.x;
#pragma unroll
        for (int o = 16; o > 0; o >>= 1) M = fmaxf(M, __shfl_xor_sync(0xffffffffu, M, o));
        float L = exp2f((mlv.x - M) * LOG2E) * mlv.y;
#pragma unroll
        for (int o = 16; o > 0; o >>= 1) L += __shfl_xor_sync(0xffffffffu, L, o);
        const float inv = 1.f / L;
        if (t == 0) {
            float p[4];
#pragma unroll
            for (int i = 0; i < 4; i++) p[i] = exp2f((sc[i] - M) * LOG2E) * inv;
            *reinterpret_cast<uint2*>(smem + OFF_PS + (warp * 4 + (g & 3)) * 16 + (g >> 2) * 8) =
                make_uint2(pack_bf2(p[0], p[1]), pack_bf2(p[2], p[3]));
        }
        __syncwarp();
        if (lane == 0) mbar_arrive(BAR(B_P));
        if (tid == 0) TSTAMP(3);
    }
    if (warp < 4) {
        const uint32_t oaddr = mapa(sbase + OFF_OPART + r * 192, rb + warp), obar = mapa(BAR(B_O), rb + warp);
        const int vr = (lane & 7) + (lane >> 4) * 8;
        uint32_t va[3];
#pragma unroll
        for (int j = 0; j < 3; j++) {
            const int mt = warp * 3 + j, line = vr * 3 + (mt >> 2);
            va[j] = sbase + line * 128 + ((((mt & 3) * 2 + ((lane >> 3) & 1)) ^ (line & 7)) << 4);
        }
        float acc[3][4];
#pragma unroll
        for (int j = 0; j < 3; j++) acc[j][0] = acc[j][1] = acc[j][2] = acc[j][3] = 0.f;
        mbar_wait(BAR(B_P));
#pragma unroll 1
        for (int s = 0; s < 8; s++) {
            const uint4 bp = lds128(sbase + OFF_PS + (s * 4 + t) * 16);
            mbar_wait(BAR(B_FULL + 16 + s));
            uint32_t a[6][4];
#pragma unroll
            for (int j = 0; j < 3; j++) {
                ldsm4t(a[j * 2], va[j] + s * SLOT);
                ldsm4t(a[j * 2 + 1], va[j] + s * SLOT + 6144);
            }
#pragma unroll
            for (int j = 0; j < 3; j++) mma16816(acc[j], a[j * 2][0], a[j * 2][1], a[j * 2][2], a[j * 2][3], bp.x, bp.y);
#pragma unroll
            for (int j = 0; j < 3; j++) mma16816(acc[j], a[j * 2 + 1][0], a[j * 2 + 1][1], a[j * 2 + 1][2], a[j * 2 + 1][3], bp.z, bp.w);
            __syncwarp();
            if (lane == 0 && s < 7) mbar_arrive(BAR(B_EMPTY + 16 + s));
        }
        if (t == 0) {
            st_async4(oaddr + g * 16, acc[0][0], acc[0][2], acc[1][0], acc[1][2], obar);
            st_async2(oaddr + 128 + (g & 3) * 16 + (g >> 2) * 8, acc[2][0], acc[2][2], obar);
        }
        if (tid == 0) TSTAMP(10);
    }
    mbar_wait(BAR(B_T));
    const uint32_t tag = lds32(sbase + OFF_GATE + 8);
    {
        const int lk = lane & 7, lh = lane >> 4, lc = (lane >> 3) & 1;
        const int lro = (lk >> 1) + (lk & 1) * 4 + lh * 8;
        const uint32_t wob = sbase + (warp >> 1) * SLOT + (warp & 1) * 6144 + lro * 128;
        const uint32_t swo = (lro & 7) ^ lc;
        uint32_t* dst = reinterpret_cast<uint32_t*>(g_box) + ((size_t)(warp * 8 + t * 2) * NCTA + b) * 8 + g;
        mbar_wait(BAR(B_O));
        if (tid == 0) TSTAMP(4);
        uint32_t bc[3][2];
        {
            float4 f[3];
#pragma unroll
            for (int i = 0; i < 3; i++) {
                const uint32_t a = sbase + OFF_OPART + i * 64 + t * 16;
                const float4 a0 = lds128f(a), a1 = lds128f(a + 192), a2 = lds128f(a + 384), a3 = lds128f(a + 576);
                f[i] = make_float4((a0.x + a1.x) + (a2.x + a3.x), (a0.y + a1.y) + (a2.y + a3.y),
                                   (a0.z + a1.z) + (a2.z + a3.z), (a0.w + a1.w) + (a2.w + a3.w));
            }
            bc[0][0] = pack_bf2(f[0].x, f[1].x); bc[0][1] = pack_bf2(f[0].y, f[1].y);
            bc[1][0] = pack_bf2(f[0].z, f[1].z); bc[1][1] = pack_bf2(f[0].w, f[1].w);
            bc[2][0] = pack_bf2(f[2].x, f[2].z); bc[2][1] = pack_bf2(f[2].y, f[2].w);
        }
        float acc[4][4];
#pragma unroll
        for (int mt = 0; mt < 4; mt++) acc[mt][0] = acc[mt][1] = acc[mt][2] = acc[mt][3] = 0.f;
        mbar_wait(BAR(B_FULL + 24 + (warp >> 1)));
#pragma unroll
        for (int ks = 0; ks < 3; ks++) {
#pragma unroll
            for (int mt = 0; mt < 4; mt++) {
                uint32_t a[4];
                ldsm4t(a, wob + ks * 2048 + ((swo ^ (mt * 2)) << 4));
                mma16816(acc[mt], a[0], a[1], a[2], a[3], bc[ks][0], bc[ks][1]);
            }
        }
        float r0 = 0.f, r1 = 0.f;
#pragma unroll
        for (int mt = 0; mt < 4; mt++)
            if (t == mt) { r0 = acc[mt][0]; r1 = acc[mt][2]; }
        st_relaxed(dst, (__float_as_uint(r0) & ~1u) | tag);
        st_relaxed(dst + NCTA * 8, (__float_as_uint(r1) & ~1u) | tag);
        if (tid == 0) TSTAMP(6);
    }
    if (warp >= 5) {
        const uint32_t raddr = mapa(sbase + OFF_REC + cr * 32 + t * 8, warp - 5), rbar = mapa(BAR(B_W), warp - 5);
        const uint32_t wa = sbase + 5 * SLOT + lane * 80 + (warp - 5) * 16;
        uint4 hf[6];
#pragma unroll
        for (int i = 0; i < 6; i++) hf[i] = lds128(sbase + OFF_HB + i * 64 + t * 16);
        float acc[6][4];
#pragma unroll
        for (int i = 0; i < 6; i++) acc[i][0] = acc[i][1] = acc[i][2] = acc[i][3] = 0.f;
#pragma unroll
        for (int s = 0; s < 2; s++) {
            mbar_wait(BAR(B_FULL + 29 + s));
#pragma unroll
            for (int i = 0; i < 3; i++) {
                uint32_t w[4];
                ldsm4t(w, wa + s * SLOT + i * 2560);
                const uint4 a = hf[s * 3 + i];
                mma16816(acc[i * 2], a.x, a.x, a.y, a.y, w[0], w[1]);
                mma16816(acc[i * 2 + 1], a.z, a.z, a.w, a.w, w[2], w[3]);
            }
        }
        const float s0 = ((acc[0][0] + acc[1][0]) + (acc[2][0] + acc[3][0])) + (acc[4][0] + acc[5][0]);
        const float s1 = ((acc[0][1] + acc[1][1]) + (acc[2][1] + acc[3][1])) + (acc[4][1] + acc[5][1]);
        if (lane < 4) st_async2(raddr, s0, s1, rbar);
    } else if (warp < 4 && cr < 5) {
        const uint4* box = g_box + (size_t)oct * (NCTA * 2) + warp * 64 + lane;
        uint4 v[2];
        uint32_t pend = 3u;
        if (lane < PSTART) mbar_wait(BAR(B_FULL + 24 + lane));
        __syncwarp();
        if (PWAIT) { const uint32_t t0 = clock(); while (clock() - t0 < PWAIT) {} }
        for (uint32_t n = 0; n < SPIN_LIMIT; n++) {
            if (PBACK && n) { const uint32_t t0 = clock(); while (clock() - t0 < PBACK) {} }
            ld_relaxed4_if(v[0], box, pend & 1u);
            ld_relaxed4_if(v[1], box + 32, pend & 2u);
            pend = (((v[0].x ^ tag) | (v[0].y ^ tag) | (v[0].z ^ tag) | (v[0].w ^ tag)) & 1u) |
                   (((v[1].x ^ tag) | (v[1].y ^ tag) | (v[1].z ^ tag) | (v[1].w ^ tag)) & 1u) * 2u;
            if (!__any_sync(0xffffffffu, pend)) break;
        }
        const float vx = __uint_as_float(v[0].x) + __uint_as_float(v[1].x), vy = __uint_as_float(v[0].y) + __uint_as_float(v[1].y);
        const float vz = __uint_as_float(v[0].z) + __uint_as_float(v[1].z), vw = __uint_as_float(v[0].w) + __uint_as_float(v[1].w);
        const bool b1 = lane & 2, b2 = lane & 4;
        float k0 = b1 ? vz : vx, k1 = b1 ? vw : vy;
        k0 += __shfl_xor_sync(0xffffffffu, b1 ? vx : vz, 2);
        k1 += __shfl_xor_sync(0xffffffffu, b1 ? vy : vw, 2);
        float s = b2 ? k1 : k0;
        s += __shfl_xor_sync(0xffffffffu, b2 ? k0 : k1, 4);
        s += __shfl_xor_sync(0xffffffffu, s, 8);
        s += __shfl_xor_sync(0xffffffffu, s, 16);
        if (lane < 8) {
            const int col = (lane & 1) * 4 + (lane & 2) + (lane >> 2);
            asm volatile("st.shared.f32 [%0], %1;" ::"r"(sbase + OFF_FIN + col * 16 + warp * 4), "f"(s) : "memory");
            mbar_arrive(BAR(B_W));
        }
    }
#undef BAR
}

typedef CUresult (*EncodeTiledFn)(CUtensorMap*, CUtensorMapDataType, cuuint32_t, void*, const cuuint64_t*, const cuuint64_t*,
                                  const cuuint32_t*, const cuuint32_t*, CUtensorMapInterleave, CUtensorMapSwizzle,
                                  CUtensorMapL2promotion, CUtensorMapFloatOOBfill);

void make_map(EncodeTiledFn fn, CUtensorMap* m, const void* ptr, uint64_t cols, uint64_t rows, uint32_t box_c, uint32_t box_r,
              int promo = 0) {
    cuuint64_t dims[2] = {cols, rows};
    cuuint64_t strides[1] = {cols * 2};
    cuuint32_t box[2] = {box_c, box_r};
    cuuint32_t es[2] = {1, 1};
    fn(m, CU_TENSOR_MAP_DATA_TYPE_BFLOAT16, 2, const_cast<void*>(ptr), dims, strides, box, es, CU_TENSOR_MAP_INTERLEAVE_NONE,
       CU_TENSOR_MAP_SWIZZLE_NONE, (CUtensorMapL2promotion)promo, CU_TENSOR_MAP_FLOAT_OOB_FILL_NONE);
}

void make_map3(EncodeTiledFn fn, CUtensorMap* m, const void* ptr, uint64_t cols, uint64_t rows, uint32_t box_r, uint32_t box_b) {
    cuuint64_t dims[3] = {64, rows, cols / 64};
    cuuint64_t strides[2] = {cols * 2, 128};
    cuuint32_t box[3] = {64, box_r, box_b};
    cuuint32_t es[3] = {1, 1, 1};
    fn(m, CU_TENSOR_MAP_DATA_TYPE_BFLOAT16, 3, const_cast<void*>(ptr), dims, strides, box, es, CU_TENSOR_MAP_INTERLEAVE_NONE,
       CU_TENSOR_MAP_SWIZZLE_128B, CU_TENSOR_MAP_L2_PROMOTION_NONE, CU_TENSOR_MAP_FLOAT_OOB_FILL_NONE);
}

void make_map3r(EncodeTiledFn fn, CUtensorMap* m, const void* ptr, uint64_t cols, uint64_t rows, uint32_t box_b, uint32_t box_r) {
    cuuint64_t dims[3] = {64, cols / 64, rows};
    cuuint64_t strides[2] = {128, cols * 2};
    cuuint32_t box[3] = {64, box_b, box_r};
    cuuint32_t es[3] = {1, 1, 1};
    fn(m, CU_TENSOR_MAP_DATA_TYPE_BFLOAT16, 3, const_cast<void*>(ptr), dims, strides, box, es, CU_TENSOR_MAP_INTERLEAVE_NONE,
       CU_TENSOR_MAP_SWIZZLE_128B, CU_TENSOR_MAP_L2_PROMOTION_NONE, CU_TENSOR_MAP_FLOAT_OOB_FILL_NONE);
}

}

extern "C" void kernel_launch(void* const* d_in, const int* in_sizes, int n_in, void* d_out, int out_size) {
    (void)in_sizes; (void)n_in; (void)out_size;
    static EncodeTiledFn encode = nullptr;
    if (!encode) {
        cudaFuncSetAttribute(fused_decode_kernel, cudaFuncAttributeMaxDynamicSharedMemorySize, SMEM_BYTES);
        void* fn = nullptr;
        cudaDriverEntryPointQueryResult qr;
        cudaGetDriverEntryPoint("cuTensorMapEncodeTiled", &fn, cudaEnableDefault, &qr);
        encode = (EncodeTiledFn)fn;
    }
    CUtensorMap mq, mg, mu, mv, mo, md;
    make_map(encode, &mq, d_in[3], NHEAD * DHEAD, D_MODEL, DHEAD, 32);
    make_map(encode, &mg, d_in[6], DFF, D_MODEL, 48, 32, GUPROMO);
    make_map(encode, &mu, d_in[7], DFF, D_MODEL, 48, 32, GUPROMO);
    make_map3r(encode, &mv, d_in[2], DHEAD, (uint64_t)NHEAD * SK, 3, 32);
    make_map3(encode, &mo, d_in[4], D_MODEL, NHEAD * DHEAD, 48, 2);
    make_map(encode, &md, d_in[8], D_MODEL, DFF, 40, 96, WDPROMO);
    const __nv_bfloat16* x  = (const __nv_bfloat16*)d_in[0];
    const __nv_bfloat16* kc = (const __nv_bfloat16*)d_in[1];
    const __nv_bfloat16* gw = (const __nv_bfloat16*)d_in[9];
    fused_decode_kernel<<<NCTA, NTHREADS, SMEM_BYTES>>>(mq, mg, mu, mv, mo, md, x, kc, gw, (const __nv_bfloat16*)d_in[8],
                                                        (__nv_bfloat16*)d_out TUNE_ARG);
}
```

```cpp
#include <cuda_runtime.h>
#include <cuda.h>
#include <cuda_bf16.h>
#include <stdint.h>

namespace {

constexpr int D_MODEL = 640;
constexpr int NHEAD   = 32;
constexpr int DHEAD   = 192;
constexpr int SK      = 4096;
constexpr int WIN     = 1024;
constexpr int DFF     = 1536;

constexpr int LQ     = 1;
constexpr int DEPTH  = 3;
constexpr int DMIN   = 3;
constexpr int DMAX   = 6;
constexpr int PI0    = 1200;
constexpr int PTS    = 490;
constexpr int WDELAY = 350;
constexpr int TOUCH  = 20;
constexpr int PSTART = 6;

constexpr int NCTA     = 128;
constexpr int NTHREADS = 384;

constexpr int SLOT      = 12288;
constexpr int OFF_QPART = 8 * SLOT;
constexpr int OFF_RED1  = OFF_QPART + 3072;
constexpr int OFF_OPART = OFF_RED1 + 1536;
constexpr int OFF_PS    = OFF_OPART + 768;
constexpr int OFF_QS    = OFF_PS + 512;
constexpr int OFF_GUP   = OFF_QS + 384;
constexpr int OFF_ML    = OFF_GUP + 768;
constexpr int OFF_HB    = OFF_ML + 256;
constexpr int OFF_REC   = OFF_HB + 384;
constexpr int OFF_FIN   = OFF_REC + 256;
constexpr int OFF_GATE  = OFF_FIN + 128;
constexpr int OFF_XS    = OFF_GATE + 16;
constexpr int OFF_BAR   = OFF_XS + 640;
constexpr int NSTAGE = 31, NEMPTY = 23;
constexpr int B_FULL = 0, B_EMPTY = 31, B_Q = 54, B_Q2 = 55, B_GU = 56, B_ML = 57, B_P = 58, B_O = 59, B_T = 60, B_W = 61, NBAR = 62;
constexpr int SMEM_BYTES = OFF_BAR + NBAR * 8;
static_assert(SMEM_BYTES <= 115712, "two CTAs must fit on one SM");

__device__ __align__(4096) uint4 g_box[80 * NCTA * 2];
__device__ __align__(1024) uint4 g_hid[NCTA * 4];
__device__ uint32_t g_epoch;

constexpr uint32_t SPIN_LIMIT = 1u << 22;

__device__ __forceinline__ uint32_t smem_u32(const void* p) { return (uint32_t)__cvta_generic_to_shared(p); }
__device__ __forceinline__ void mbar_init(uint32_t bar, int cnt) {
    asm volatile("mbarrier.init.shared::cta.b64 [%0], %1;" ::"r"(bar), "r"(cnt) : "memory");
}
__device__ __forceinline__ void mbar_expect(uint32_t bar, uint32_t bytes) {
    asm volatile("mbarrier.arrive.expect_tx.shared::cta.b64 _, [%0], %1;" ::"r"(bar), "r"(bytes) : "memory");
}
__device__ __forceinline__ void mbar_arrive(uint32_t bar) {
    asm volatile("mbarrier.arrive.shared::cta.b64 _, [%0];" ::"r"(bar) : "memory");
}
__device__ __forceinline__ bool mbar_try(uint32_t bar) {
    uint32_t ok;
    asm volatile("{\n .reg .pred p;\n mbarrier.try_wait.parity.shared::cta.b64 p, [%1], 0;\n selp.u32 %0, 1, 0, p;\n }"
                 : "=r"(ok) : "r"(bar) : "memory");
    return ok != 0;
}
__device__ __forceinline__ bool mbar_test(uint32_t bar) {
    uint32_t ok;
    asm volatile("{\n .reg .pred p;\n mbarrier.test_wait.parity.shared::cta.b64 p, [%1], 0;\n selp.u32 %0, 1, 0, p;\n }"
                 : "=r"(ok) : "r"(bar) : "memory");
    return ok != 0;
}
__device__ __forceinline__ void mbar_wait(uint32_t bar) {
    uint32_t n = 0;
    while (!mbar_try(bar)) { if (++n > SPIN_LIMIT) break; }
}
__device__ __forceinline__ uint32_t mapa(uint32_t addr, uint32_t rank) {
    uint32_t r;
    asm("mapa.shared::cluster.u32 %0, %1, %2;" : "=r"(r) : "r"(addr), "r"(rank));
    return r;
}
__device__ __forceinline__ void st_async4(uint32_t addr, float a, float b, float c, float d, uint32_t bar) {
    asm volatile("st.async.weak.shared::cluster.mbarrier::complete_tx::bytes.v4.f32 [%0], {%1,%2,%3,%4}, [%5];"
                 ::"r"(addr), "f"(a), "f"(b), "f"(c), "f"(d), "r"(bar) : "memory");
}
__device__ __forceinline__ void st_async2(uint32_t addr, float a, float b, uint32_t bar) {
    asm volatile("st.async.weak.shared::cluster.mbarrier::complete_tx::bytes.v2.f32 [%0], {%1,%2}, [%3];"
                 ::"r"(addr), "f"(a), "f"(b), "r"(bar) : "memory");
}
constexpr uint64_t EVICT_FIRST = 0x12F0000000000000ull;
__device__ __forceinline__ void bulk_g2s(uint32_t dst, const void* src, uint32_t bytes, uint32_t bar) {
    asm volatile("cp.async.bulk.shared::cluster.global.mbarrier::complete_tx::bytes.L2::cache_hint [%0], [%1], %2, [%3], %4;"
                 ::"r"(dst), "l"(src), "r"(bytes), "r"(bar), "l"(EVICT_FIRST) : "memory");
}
__device__ __forceinline__ void tensor_g2s(uint32_t dst, const CUtensorMap* map, int c0, int c1, uint32_t bar) {
    asm volatile("cp.async.bulk.tensor.2d.shared::cluster.global.mbarrier::complete_tx::bytes.L2::cache_hint [%0], [%1, {%3, %4}], [%2], %5;"
                 ::"r"(dst), "l"(map), "r"(bar), "r"(c0), "r"(c1), "l"(EVICT_FIRST) : "memory");
}
__device__ __forceinline__ void tensor3_g2s(uint32_t dst, const CUtensorMap* map, int c1, int c2, uint32_t bar) {
    asm volatile("cp.async.bulk.tensor.3d.shared::cluster.global.mbarrier::complete_tx::bytes.L2::cache_hint [%0], [%1, {%3, %4, %5}], [%2], %6;"
                 ::"r"(dst), "l"(map), "r"(bar), "r"(0), "r"(c1), "r"(c2), "l"(EVICT_FIRST) : "memory");
}
__device__ __forceinline__ void ldsm4t(uint32_t (&a)[4], uint32_t addr) {
    asm volatile("ldmatrix.sync.aligned.m8n8.x4.trans.shared.b16 {%0,%1,%2,%3}, [%4];"
                 : "=r"(a[0]), "=r"(a[1]), "=r"(a[2]), "=r"(a[3]) : "r"(addr));
}
__device__ __forceinline__ uint32_t lds32(uint32_t addr) {
    uint32_t v;
    asm volatile("ld.shared.u32 %0, [%1];" : "=r"(v) : "r"(addr));
    return v;
}
__device__ __forceinline__ void st_relaxed(uint32_t* p, uint32_t v) {
    asm volatile("st.relaxed.gpu.global.u32 [%0], %1;" ::"l"(p), "r"(v) : "memory");
}
__device__ __forceinline__ uint32_t ld_relaxed(const uint32_t* p) {
    uint32_t v;
    asm volatile("ld.relaxed.gpu.global.u32 %0, [%1];" : "=r"(v) : "l"(p) : "memory");
    return v;
}
__device__ __forceinline__ uint4 ld_relaxed4(const uint4* p) {
    uint4 v;
    asm volatile("ld.relaxed.gpu.global.v4.u32 {%0,%1,%2,%3}, [%4];"
                 : "=r"(v.x), "=r"(v.y), "=r"(v.z), "=r"(v.w) : "l"(p) : "memory");
    return v;
}
__device__ __forceinline__ void st_relaxed4(uint4* p, uint4 v) {
    asm volatile("st.relaxed.gpu.global.v4.u32 [%0], {%1,%2,%3,%4};" ::"l"(p), "r"(v.x), "r"(v.y), "r"(v.z), "r"(v.w) : "memory");
}
__device__ __forceinline__ uint4 ldg_stream(const void* p) {
    uint4 v;
    asm volatile("ld.global.nc.L1::no_allocate.v4.u32 {%0,%1,%2,%3}, [%4];"
                 : "=r"(v.x), "=r"(v.y), "=r"(v.z), "=r"(v.w) : "l"(p));
    return v;
}
__device__ __forceinline__ void bar_sync(int id, int n) { asm volatile("bar.sync %0, %1;" ::"r"(id), "r"(n) : "memory"); }
__device__ __forceinline__ float bf_lo(uint32_t w) { return __uint_as_float(w << 16); }
__device__ __forceinline__ float bf_hi(uint32_t w) { return __uint_as_float(w & 0xffff0000u); }
__device__ __forceinline__ float bfr(float f) {
    uint32_t u;
    asm("cvt.rn.bf16x2.f32 %0, %1, %2;" : "=r"(u) : "f"(f), "f"(0.f));
    return __uint_as_float(u);
}
__device__ __forceinline__ uint32_t pack_bf2(float lo, float hi) {
    __nv_bfloat162 t = __floats2bfloat162_rn(lo, hi);
    return *reinterpret_cast<uint32_t*>(&t);
}
__device__ __forceinline__ void mma16816(float (&c)[4], uint32_t a0, uint32_t a1, uint32_t a2, uint32_t a3,
                                         uint32_t b0, uint32_t b1) {
    asm volatile("mma.sync.aligned.m16n8k16.row.col.f32.bf16.bf16.f32 {%0,%1,%2,%3}, {%4,%5,%6,%7}, {%8,%9}, {%0,%1,%2,%3};"
                 : "+f"(c[0]), "+f"(c[1]), "+f"(c[2]), "+f"(c[3])
                 : "r"(a0), "r"(a1), "r"(a2), "r"(a3), "r"(b0), "r"(b1));
}
__device__ __forceinline__ uint4 lds128(uint32_t addr) {
    uint4 v;
    asm volatile("ld.shared.v4.u32 {%0,%1,%2,%3}, [%4];" : "=r"(v.x), "=r"(v.y), "=r"(v.z), "=r"(v.w) : "r"(addr));
    return v;
}
__device__ __forceinline__ float4 lds128f(uint32_t addr) {
    float4 v;
    asm volatile("ld.shared.v4.f32 {%0,%1,%2,%3}, [%4];" : "=f"(v.x), "=f"(v.y), "=f"(v.z), "=f"(v.w) : "r"(addr));
    return v;
}
__device__ __forceinline__ void fma8(float (&acc)[8], float xv, const uint4& w) {
    acc[0] = fmaf(xv, bf_lo(w.x), acc[0]); acc[1] = fmaf(xv, bf_hi(w.x), acc[1]);
    acc[2] = fmaf(xv, bf_lo(w.y), acc[2]); acc[3] = fmaf(xv, bf_hi(w.y), acc[3]);
    acc[4] = fmaf(xv, bf_lo(w.z), acc[4]); acc[5] = fmaf(xv, bf_hi(w.z), acc[5]);
    acc[6] = fmaf(xv, bf_lo(w.w), acc[6]); acc[7] = fmaf(xv, bf_hi(w.w), acc[7]);
}

__device__ __forceinline__ void ld_relaxed4_if(uint4& v, const uint4* p, uint32_t cond) {
    asm volatile("{\n .reg .pred p;\n setp.ne.u32 p, %5, 0;\n @p ld.relaxed.gpu.global.v4.u32 {%0,%1,%2,%3}, [%4];\n}"
                 : "+r"(v.x), "+r"(v.y), "+r"(v.z), "+r"(v.w) : "l"(p), "r"(cond) : "memory");
}
__device__ __forceinline__ uint32_t timer_ns() {
    uint32_t t;
    asm volatile("mov.u32 %0, %globaltimer_lo;" : "=r"(t));
    return t;
}

template <int G>
__device__ __forceinline__ void init_bars(uint32_t bar0) {
    constexpr int N = (NBAR - LQ - DEPTH + 4) / 5;
#pragma unroll
    for (int k = 0; k < N; k++) {
        const int i = LQ + DEPTH + G * N + k;
        if (i >= NBAR || (i >= B_EMPTY && i < B_EMPTY + LQ)) continue;
        int cnt = 1;
        if (i >= B_EMPTY && i < B_EMPTY + 8) cnt = i < B_EMPTY + 5 ? 6 : 3;
        if (i >= B_EMPTY + 16 && i < B_EMPTY + NEMPTY) cnt = 4;
        if (i == B_Q2 || i == B_T) cnt = 32;
        if (i == B_GU) cnt = 2;
        if (i == B_P) cnt = 8;
        if (i == B_W) cnt = 33;
        mbar_init(bar0 + i * 8, cnt);
        if (i == B_Q)  mbar_expect(bar0 + i * 8, 4 * 768);
        if (i == B_GU) mbar_expect(bar0 + i * 8, 8 * 96);
        if (i == B_ML) mbar_expect(bar0 + i * 8, 32 * 8);
        if (i == B_O)  mbar_expect(bar0 + i * 8, 4 * 192);
        if (i == B_W)  mbar_expect(bar0 + i * 8, 8 * 32);
    }
}

struct Maps { CUtensorMap m[6]; };

__global__ void __cluster_dims__(8, 1, 1) __launch_bounds__(NTHREADS, 2)
fused_decode_kernel(const __grid_constant__ Maps maps,
                    const __nv_bfloat16* __restrict__ x, const __nv_bfloat16* __restrict__ kc,
                    const __nv_bfloat16* __restrict__ gate_w, const __nv_bfloat16* __restrict__ wq,
                    __nv_bfloat16* __restrict__ out) {
    extern __shared__ __align__(1024) unsigned char smem[];
    const uint32_t sbase = smem_u32(smem);
    const int tid = threadIdx.x, warp = tid >> 5, lane = tid & 31;
    const int b = blockIdx.x, h = b >> 2, r = b & 3;
    const int cr = b & 7, rb = b & 4;
    const int oct = (b >> 3) * 5 + cr;
    const float LOG2E = 1.4426950408889634f;
    const uint32_t bar0 = sbase + OFF_BAR;
#define BAR(i) (bar0 + (i) * 8)

    uint4 w0[LQ * 4];
    if (warp < 6) {
        const __nv_bfloat16* src = wq + (size_t)(r * 32 + (warp / 3) * 16 + (lane >> 3)) * (NHEAD * DHEAD) + h * DHEAD +
                                   (warp % 3) * 64 + (lane & 7) * 8;
#pragma unroll
        for (int i = 0; i < LQ * 4; i++) {
            w0[i] = ldg_stream(src + (size_t)((i >> 2) * 128 + (i & 3) * 4) * (NHEAD * DHEAD));
        }
    }

    if (warp == 10) {
        const uint32_t due = timer_ns() + PI0 + (lane - 4) * PTS - (lane > 7 ? PTS / 2 : 0) - (lane > 29 ? PTS * 3 / 8 : 0) +
                             (lane > 28 ? WDELAY : 0);
        if (lane == 0) asm volatile("prefetch.tensormap [%0];" ::"l"(&maps.m[0]) : "memory");
        const uint32_t dst = sbase + (lane & 7) * SLOT, fb = BAR(B_FULL + (lane < NSTAGE ? lane : 0));
        if (lane == 0) {
#pragma unroll
            for (int i = LQ; i < LQ + DEPTH; i++) mbar_init(BAR(B_FULL + i), 1);
        }
        asm volatile("fence.mbarrier_init.release.cluster;" ::: "memory");
        asm volatile("fence.proxy.async.shared::cta;" ::: "memory");
        __syncwarp();
        asm volatile("barrier.cluster.arrive.relaxed;" ::: "memory");
        const size_t key = (size_t)h * SK + (SK - WIN) + ((lane & 7) * 4 + r) * 32;
        auto issue = [&]() {
            if (lane < 5) {
                mbar_expect(fb, 12288);
                tensor_g2s(dst, &maps.m[0], h * DHEAD, lane * 128 + r * 32, fb);
            } else if (lane < 8) {
                mbar_expect(fb, lane < 7 ? 12288 : 6144);
#pragma unroll 1
                for (int k = 0; k < (lane < 7 ? 4 : 2); k++) {
                    const int j = (lane - 5) * 4 + k;
                    tensor_g2s(dst + k * 3072, &maps.m[j < 5 ? 1 : 2], (b >> 3) * 96,
                               (j < 5 ? j : j - 5) * 128 + r * 32 + (cr >> 2) * 16, fb);
                }
            } else if (lane < 16) {
                mbar_expect(fb, 12288);
                bulk_g2s(dst, kc + key * DHEAD, 12288, fb);
            } else if (lane < 24) {
                mbar_expect(fb, 12288);
                tensor3_g2s(dst, &maps.m[3], 0, (int)key, fb);
            } else if (lane < 29) {
                mbar_expect(fb, 12288);
                tensor3_g2s(dst, &maps.m[4], h * DHEAD + r * 48, (lane - 24) * 2, fb);
            } else {
                mbar_expect(fb, 7680);
                tensor_g2s(dst, &maps.m[5], (b >> 3) * 40, (lane - 29) * 768 + cr * 96, fb);
            }
        };
        static_assert(LQ + DEPTH <= 5, "initial stages: wq only");
        if (lane == 0) {
#pragma unroll
            for (int i = LQ; i < LQ + DEPTH; i++) {
                const uint32_t d = sbase + i * SLOT, bb = BAR(B_FULL + i);
                mbar_expect(bb, 12288);
                tensor_g2s(d, &maps.m[0], h * DHEAD, i * 128 + r * 32, bb);
            }
        }
        if (lane == 0) {
#pragma unroll
            for (int i = 1; i < 6; i++) asm volatile("prefetch.tensormap [%0];" ::"l"(&maps.m[i]) : "memory");
        }
        __syncwarp();
        bar_sync(4, 192);
        int nxt = LQ + DEPTH;
        uint32_t n = 0;
        bool f = lane < LQ, e = lane >= NEMPTY || lane < LQ;
        while (nxt < NSTAGE) {
            if (!f && lane < nxt) f = mbar_test(fb);
            if (!e && (unsigned)(lane + 8 - nxt) < 2u) e = mbar_test(BAR(B_EMPTY + lane));
            const uint32_t em = __ballot_sync(0xffffffffu, e);
            const uint32_t tm = __ballot_sync(0xffffffffu, (int)(timer_ns() - due) >= 0);
            const int c = __popc(__ballot_sync(0xffffffffu, f));
            while (nxt < NSTAGE && nxt < c + (((tm >> nxt) & 1u) ? DMAX : DMIN) &&
                   (nxt < 8 || ((em >> (nxt - 8)) & 1u))) {
                if (lane == nxt) issue();
                __syncwarp();
                nxt++;
            }
            if (++n > SPIN_LIMIT) break;
        }
        asm volatile("barrier.cluster.wait.acquire;" ::: "memory");
        return;
    }

    if (warp >= 6) {
        if (lane == 0) {
            if (warp == 6) init_bars<0>(bar0);
            else if (warp == 7) init_bars<1>(bar0);
            else if (warp == 8) init_bars<2>(bar0);
            else if (warp == 9) init_bars<3>(bar0);
            else init_bars<4>(bar0);
            asm volatile("fence.mbarrier_init.release.cluster;" ::: "memory");
            asm volatile("fence.proxy.async.shared::cta;" ::: "memory");
        }
        __syncwarp();
        asm volatile("bar.arrive 4, 192;" ::: "memory");
    }
    asm volatile("barrier.cluster.arrive.relaxed;" ::: "memory");

    if (warp == 11) {
        const uint32_t epoch = ld_relaxed(&g_epoch), tag16 = (epoch + 1u) & 0xffffu;
        asm volatile("barrier.cluster.wait.acquire;" ::: "memory");
        mbar_wait(BAR(B_Q));
#pragma unroll
        for (int k = 0; k < 2; k++) {
            const int j = lane + k * 32;
            if (j < 48) {
                const float4 a0 = lds128f(sbase + OFF_QPART + j * 16), a1 = lds128f(sbase + OFF_QPART + 768 + j * 16);
                const float4 a2 = lds128f(sbase + OFF_QPART + 1536 + j * 16), a3 = lds128f(sbase + OFF_QPART + 2304 + j * 16);
                *reinterpret_cast<uint2*>(smem + OFF_QS + j * 8) =
                    make_uint2(pack_bf2((a0.x + a1.x) + (a2.x + a3.x), (a0.y + a1.y) + (a2.y + a3.y)),
                               pack_bf2((a0.z + a1.z) + (a2.z + a3.z), (a0.w + a1.w) + (a2.w + a3.w)));
            }
        }
        mbar_arrive(BAR(B_Q2));
        mbar_wait(BAR(B_GU));
        if (lane < 16) {
            const float2* gp = reinterpret_cast<const float2*>(smem + OFF_GUP) + (lane < 12 ? lane : 0);
            const float2 p0 = gp[0], p1 = gp[12], p2 = gp[24], p3 = gp[36], p4 = gp[48], p5 = gp[60], p6 = gp[72], p7 = gp[84];
            const float gv = bfr(((p0.x + p1.x) + (p2.x + p3.x)) + ((p4.x + p5.x) + (p6.x + p7.x)));
            const float uv = bfr(((p0.y + p1.y) + (p2.y + p3.y)) + ((p4.y + p5.y) + (p6.y + p7.y)));
            const float inner = 0.7978845608028654f * (gv + 0.044715f * gv * gv * gv);
            const float ge = bfr(0.5f * gv * (1.f + tanhf(inner)));
            st_relaxed(reinterpret_cast<uint32_t*>(g_hid) + b * 16 + lane, __float_as_uint(bfr(ge * uv)) | tag16);
        } else if (lane == 16) *reinterpret_cast<uint32_t*>(smem + OFF_GATE + 8) = tag16 & 1u;
        const float2 gt = *reinterpret_cast<const float2*>(smem + OFF_GATE);
        mbar_wait(BAR(B_FULL + TOUCH));
        {
            const uint4* hp = g_hid + cr * 32 + lane;
            uint4* ib = g_box + ((size_t)(lane >> 1) * NCTA + b) * 2 + (lane & 1);
            constexpr int ISTR = 16 * NCTA * 2;
            uint4 v[2];
            v[0] = ld_relaxed4(hp);
            v[1] = ld_relaxed4(hp + 256);
#pragma unroll
            for (int k = 0; k < 5; k++) st_relaxed4(ib + k * ISTR, make_uint4(0u, 1u, 0u, 1u));
#pragma unroll
            for (int k = 0; k < 2; k++) {
#pragma unroll 1
                for (uint32_t n = 0; n < SPIN_LIMIT; n++) {
                    if (!(((v[k].x ^ tag16) | (v[k].y ^ tag16) | (v[k].z ^ tag16) | (v[k].w ^ tag16)) & 0xffffu)) break;
                    v[k] = ld_relaxed4(hp + k * 256);
                }
                if ((lane & 3) != 3) {
                    const int kk = (k * 8 + (lane >> 2)) * 12 + (lane & 3) * 4;
                    const uint32_t a = sbase + OFF_HB + (kk >> 5) * 64 + ((kk & 7) >> 1) * 16 + ((kk >> 3) & 3) * 4;
                    asm volatile("st.shared.u32 [%0], %1;" ::"r"(a), "r"(__byte_perm(v[k].x, v[k].y, 0x7632)) : "memory");
                    asm volatile("st.shared.u32 [%0], %1;" ::"r"(a + 16), "r"(__byte_perm(v[k].z, v[k].w, 0x7632)) : "memory");
                }
            }
            mbar_arrive(BAR(B_T));
        }
        if (cr < 5) {
            mbar_wait(BAR(B_W));
            if (lane < 8) {
                const float4 u = lds128f(sbase + OFF_FIN + lane * 16);
                const float* rp = reinterpret_cast<const float*>(smem + OFF_REC) + lane;
                const float av = bfr((u.x + u.y) + (u.z + u.w));
                const float bv = bfr(((rp[0] + rp[8]) + (rp[16] + rp[24])) + ((rp[32] + rp[40]) + (rp[48] + rp[56])));
                out[oct * 8 + lane] = __float2bfloat16_rn(bfr(gt.x * av) + bfr(gt.y * bv));
            }
            if (b == 0 && lane == 0) st_relaxed(&g_epoch, epoch + 1u);
        }
        return;
    }

    const float* xs = reinterpret_cast<const float*>(smem + OFF_XS);
    if (tid < 160) reinterpret_cast<float*>(smem + OFF_XS)[tid] = __bfloat162float(x[(tid >> 5) * 128 + r * 32 + (tid & 31)]);
    bar_sync(3, 320);
    asm volatile("barrier.cluster.wait.acquire;" ::: "memory");
    if (warp < 6) {
        const int c3 = warp % 3, hf = warp / 3, rs = lane >> 3;
        const uint32_t a = sbase + (hf * 16 + rs) * 384 + c3 * 128 + (lane & 7) * 16;
        float acc[8];
#pragma unroll
        for (int j = 0; j < 8; j++) acc[j] = 0.f;
#pragma unroll
        for (int i = 0; i < LQ * 4; i++) fma8(acc, xs[(i >> 2) * 32 + hf * 16 + rs + (i & 3) * 4], w0[i]);
#pragma unroll 1
        for (int s = LQ; s < 5; s++) {
            float xv[4];
#pragma unroll
            for (int i = 0; i < 4; i++) xv[i] = xs[s * 32 + hf * 16 + rs + 4 * i];
            mbar_wait(BAR(B_FULL + s));
#pragma unroll
            for (int i = 0; i < 4; i++) fma8(acc, xv[i], lds128(a + s * SLOT + i * 1536));
            __syncwarp();
            if (lane == 0) mbar_arrive(BAR(B_EMPTY + s));
        }
#pragma unroll
        for (int j = 0; j < 8; j++) {
            acc[j] += __shfl_xor_sync(0xffffffffu, acc[j], 8);
            acc[j] += __shfl_xor_sync(0xffffffffu, acc[j], 16);
        }
        if (lane < 16) {
            float4* dst = reinterpret_cast<float4*>(smem + OFF_RED1 + hf * 768 + c3 * 256 + (lane & 7) * 32 + rs * 16);
            *dst = rs ? make_float4(acc[4], acc[5], acc[6], acc[7]) : make_float4(acc[0], acc[1], acc[2], acc[3]);
        }
        bar_sync(1, 192);
        const int dest = rb + tid / 48, quad = tid % 48;
        const float4 u0 = lds128f(sbase + OFF_RED1 + quad * 16), u1 = lds128f(sbase + OFF_RED1 + 768 + quad * 16);
        st_async4(mapa(sbase + OFF_QPART + r * 768 + quad * 16, dest), u0.x + u1.x, u0.y + u1.y, u0.z + u1.z,
                  u0.w + u1.w, mapa(BAR(B_Q), dest));
    } else if (warp < 9) {
        const int t = tid - 192, rg = t / 12;
        const float* xg = xs + (cr >> 2) * 16 + rg;
        float ag[8], au[8];
#pragma unroll
        for (int j = 0; j < 8; j++) { ag[j] = 0.f; au[j] = 0.f; }
#pragma unroll
        for (int s = 0; s < 3; s++) {
            const uint32_t a = sbase + (5 + s) * SLOT + t * 16;
            mbar_wait(BAR(B_FULL + 5 + s));
#pragma unroll
            for (int i = 0; i < (s < 2 ? 8 : 4); i++) {
                const int j = s * 4 + (i >> 1);
                const float xv = xg[(j < 5 ? j : j - 5) * 32 + (i & 1) * 8];
                if (j < 5) fma8(ag, xv, lds128(a + i * 1536));
                else       fma8(au, xv, lds128(a + i * 1536));
            }
            if (s < 2) {
                __syncwarp();
                if (lane == 0) mbar_arrive(BAR(B_EMPTY + 5 + s));
            }
        }
        float* red2 = reinterpret_cast<float*>(smem + 7 * SLOT + 6144);
        float4* dst = reinterpret_cast<float4*>(red2 + rg * 192 + (t % 12) * 8);
        dst[0] = make_float4(ag[0], ag[1], ag[2], ag[3]);   dst[1] = make_float4(ag[4], ag[5], ag[6], ag[7]);
        dst[24] = make_float4(au[0], au[1], au[2], au[3]);  dst[25] = make_float4(au[4], au[5], au[6], au[7]);
        bar_sync(2, 96);
        float sg = 0.f, su = 0.f;
#pragma unroll
        for (int i = 0; i < 8; i++) { sg += red2[i * 192 + t]; su += red2[i * 192 + 96 + t]; }
        st_async2(mapa(sbase + OFF_GUP + cr * 96 + (t % 12) * 8, rg), sg, su, mapa(BAR(B_GU), rg));
        asm volatile("fence.proxy.async.shared::cta;" ::: "memory");
        __syncwarp();
        if (lane == 0) mbar_arrive(BAR(B_EMPTY + 7));
    } else {
        float gs = 0.f;
        for (int c = lane; c < D_MODEL / 8; c += 32) {
            uint4 xv = *reinterpret_cast<const uint4*>(x + c * 8);
            uint4 gv = *reinterpret_cast<const uint4*>(gate_w + c * 8);
            gs += bfr(bf_lo(xv.x) * bf_lo(gv.x)) + bfr(bf_hi(xv.x) * bf_hi(gv.x));
            gs += bfr(bf_lo(xv.y) * bf_lo(gv.y)) + bfr(bf_hi(xv.y) * bf_hi(gv.y));
            gs += bfr(bf_lo(xv.z) * bf_lo(gv.z)) + bfr(bf_hi(xv.z) * bf_hi(gv.z));
            gs += bfr(bf_lo(xv.w) * bf_lo(gv.w)) + bfr(bf_hi(xv.w) * bf_hi(gv.w));
        }
#pragma unroll
        for (int o = 16; o > 0; o >>= 1) gs += __shfl_xor_sync(0xffffffffu, gs, o);
        const float gate = bfr(1.f / (1.f + __expf(-bfr(gs))));
        if (lane == 0) {
            *reinterpret_cast<float2*>(smem + OFF_GATE) = make_float2(gate, bfr(1.f - gate));
            mbar_arrive(BAR(B_GU));
        }
    }

    const int g = lane >> 2, t = lane & 3;
    if (warp < 8) {
        const int chunk = warp * 4 + r;
        const uint32_t slot = sbase + warp * SLOT;
        mbar_wait(BAR(B_Q2));
        uint32_t qf[6][4];
#pragma unroll
        for (int s = 0; s < 6; s++) {
            uint4 v = lds128(sbase + OFF_QS + (((s ^ (g & 1)) * 4 + t) * 16));
            qf[s][0] = v.x; qf[s][1] = v.y; qf[s][2] = v.z; qf[s][3] = v.w;
        }
        mbar_wait(BAR(B_FULL + 8 + warp));
        float c0[4] = {0.f, 0.f, 0.f, 0.f}, c1[4] = {0.f, 0.f, 0.f, 0.f};
        const uint32_t kb = slot + (16 * (g >> 2) + 2 * (g & 3)) * 384;
#pragma unroll
        for (int s = 0; s < 6; s++) {
            const uint32_t co = ((s ^ (g & 1)) * 4 + t) * 16;
            uint4 r0 = lds128(kb + co), r1 = lds128(kb + 384 + co), r2 = lds128(kb + 3072 + co), r3 = lds128(kb + 3456 + co);
            mma16816(c0, r0.x, r1.x, r0.y, r1.y, qf[s][0], qf[s][1]);
            mma16816(c1, r2.x, r3.x, r2.y, r3.y, qf[s][0], qf[s][1]);
            mma16816(c0, r0.z, r1.z, r0.w, r1.w, qf[s][2], qf[s][3]);
            mma16816(c1, r2.z, r3.z, r2.w, r3.w, qf[s][2], qf[s][3]);
        }
        __syncwarp();
        if (lane == 0) mbar_arrive(BAR(B_EMPTY + 8 + warp));
        const float scale = 0.07216878364870322f;
        float sc[4];
        sc[0] = (g & 1) ? c0[1] : c0[0];
        sc[1] = (g & 1) ? c0[3] : c0[2];
        sc[2] = (g & 1) ? c1[1] : c1[0];
        sc[3] = (g & 1) ? c1[3] : c1[2];
#pragma unroll
        for (int i = 0; i < 4; i++) sc[i] = bfr(bfr(sc[i]) * scale);
        float m = fmaxf(fmaxf(sc[0], sc[1]), fmaxf(sc[2], sc[3]));
#pragma unroll
        for (int o = 4; o < 32; o <<= 1) m = fmaxf(m, __shfl_xor_sync(0xffffffffu, m, o));
        float l = 0.f;
#pragma unroll
        for (int i = 0; i < 4; i++) l += exp2f((sc[i] - m) * LOG2E);
#pragma unroll
        for (int o = 4; o < 32; o <<= 1) l += __shfl_xor_sync(0xffffffffu, l, o);
        if (lane < 4) st_async2(mapa(sbase + OFF_ML + chunk * 8, rb + lane), m, l, mapa(BAR(B_ML), rb + lane));
        mbar_wait(BAR(B_ML));
        const float2 mlv = *reinterpret_cast<const float2*>(smem + OFF_ML + lane * 8);
        float M = mlv.x;
#pragma unroll
        for (int o = 16; o > 0; o >>= 1) M = fmaxf(M, __shfl_xor_sync(0xffffffffu, M, o));
        float L = exp2f((mlv.x - M) * LOG2E) * mlv.y;
#pragma unroll
        for (int o = 16; o > 0; o >>= 1) L += __shfl_xor_sync(0xffffffffu, L, o);
        const float inv = 1.f / L;
        if (t == 0) {
            float p[4];
#pragma unroll
            for (int i = 0; i < 4; i++) p[i] = exp2f((sc[i] - M) * LOG2E) * inv;
            *reinterpret_cast<uint2*>(smem + OFF_PS + (warp * 4 + (g & 3)) * 16 + (g >> 2) * 8) =
                make_uint2(pack_bf2(p[0], p[1]), pack_bf2(p[2], p[3]));
        }
        __syncwarp();
        if (lane == 0) mbar_arrive(BAR(B_P));
    }
    if (warp < 4) {
        const uint32_t oaddr = mapa(sbase + OFF_OPART + r * 192, rb + warp), obar = mapa(BAR(B_O), rb + warp);
        const int vr = (lane & 7) + (lane >> 4) * 8;
        uint32_t va[3];
#pragma unroll
        for (int j = 0; j < 3; j++) {
            const int mt = warp * 3 + j, line = vr * 3 + (mt >> 2);
            va[j] = sbase + line * 128 + ((((mt & 3) * 2 + ((lane >> 3) & 1)) ^ (line & 7)) << 4);
        }
        float acc[3][4];
#pragma unroll
        for (int j = 0; j < 3; j++) acc[j][0] = acc[j][1] = acc[j][2] = acc[j][3] = 0.f;
        mbar_wait(BAR(B_P));
#pragma unroll 1
        for (int s = 0; s < 8; s++) {
            const uint4 bp = lds128(sbase + OFF_PS + (s * 4 + t) * 16);
            mbar_wait(BAR(B_FULL + 16 + s));
            uint32_t a[6][4];
#pragma unroll
            for (int j = 0; j < 3; j++) {
                ldsm4t(a[j * 2], va[j] + s * SLOT);
                ldsm4t(a[j * 2 + 1], va[j] + s * SLOT + 6144);
            }
#pragma unroll
            for (int j = 0; j < 3; j++) mma16816(acc[j], a[j * 2][0], a[j * 2][1], a[j * 2][2], a[j * 2][3], bp.x, bp.y);
#pragma unroll
            for (int j = 0; j < 3; j++) mma16816(acc[j], a[j * 2 + 1][0], a[j * 2 + 1][1], a[j * 2 + 1][2], a[j * 2 + 1][3], bp.z, bp.w);
            __syncwarp();
            if (lane == 0 && s < 7) mbar_arrive(BAR(B_EMPTY + 16 + s));
        }
        if (t == 0) {
            st_async4(oaddr + g * 16, acc[0][0], acc[0][2], acc[1][0], acc[1][2], obar);
            st_async2(oaddr + 128 + (g & 3) * 16 + (g >> 2) * 8, acc[2][0], acc[2][2], obar);
        }
    }
    mbar_wait(BAR(B_T));
    const uint32_t tag = lds32(sbase + OFF_GATE + 8);
    {
        const int lk = lane & 7, lh = lane >> 4, lc = (lane >> 3) & 1;
        const int lro = (lk >> 1) + (lk & 1) * 4 + lh * 8;
        const uint32_t wob = sbase + (warp >> 1) * SLOT + (warp & 1) * 6144 + lro * 128;
        const uint32_t swo = (lro & 7) ^ lc;
        uint32_t* dst = reinterpret_cast<uint32_t*>(g_box) + ((size_t)(warp * 8 + t * 2) * NCTA + b) * 8 + g;
        constexpr int DSTR = NCTA * 8;
        mbar_wait(BAR(B_O));
        uint32_t bc[3][2];
        {
            float4 f[3];
#pragma unroll
            for (int i = 0; i < 3; i++) {
                const uint32_t a = sbase + OFF_OPART + i * 64 + t * 16;
                const float4 a0 = lds128f(a), a1 = lds128f(a + 192), a2 = lds128f(a + 384), a3 = lds128f(a + 576);
                f[i] = make_float4((a0.x + a1.x) + (a2.x + a3.x), (a0.y + a1.y) + (a2.y + a3.y),
                                   (a0.z + a1.z) + (a2.z + a3.z), (a0.w + a1.w) + (a2.w + a3.w));
            }
            bc[0][0] = pack_bf2(f[0].x, f[1].x); bc[0][1] = pack_bf2(f[0].y, f[1].y);
            bc[1][0] = pack_bf2(f[0].z, f[1].z); bc[1][1] = pack_bf2(f[0].w, f[1].w);
            bc[2][0] = pack_bf2(f[2].x, f[2].z); bc[2][1] = pack_bf2(f[2].y, f[2].w);
        }
        float acc[4][4];
#pragma unroll
        for (int mt = 0; mt < 4; mt++) acc[mt][0] = acc[mt][1] = acc[mt][2] = acc[mt][3] = 0.f;
        mbar_wait(BAR(B_FULL + 24 + (warp >> 1)));
#pragma unroll
        for (int ks = 0; ks < 3; ks++) {
#pragma unroll
            for (int mt = 0; mt < 4; mt++) {
                uint32_t a[4];
                ldsm4t(a, wob + ks * 2048 + ((swo ^ (mt * 2)) << 4));
                mma16816(acc[mt], a[0], a[1], a[2], a[3], bc[ks][0], bc[ks][1]);
            }
        }
        float r0 = 0.f, r1 = 0.f;
#pragma unroll
        for (int mt = 0; mt < 4; mt++)
            if (t == mt) { r0 = acc[mt][0]; r1 = acc[mt][2]; }
        st_relaxed(dst, (__float_as_uint(r0) & ~1u) | tag);
        st_relaxed(dst + DSTR, (__float_as_uint(r1) & ~1u) | tag);
    }
    if (warp >= 5) {
        const uint32_t raddr = mapa(sbase + OFF_REC + cr * 32 + t * 8, warp - 5), rbar = mapa(BAR(B_W), warp - 5);
        const uint32_t wa = sbase + 5 * SLOT + lane * 80 + (warp - 5) * 16;
        uint4 hf[6];
#pragma unroll
        for (int i = 0; i < 6; i++) hf[i] = lds128(sbase + OFF_HB + i * 64 + t * 16);
        float acc[6][4];
#pragma unroll
        for (int i = 0; i < 6; i++) acc[i][0] = acc[i][1] = acc[i][2] = acc[i][3] = 0.f;
#pragma unroll
        for (int s = 0; s < 2; s++) {
            mbar_wait(BAR(B_FULL + 29 + s));
#pragma unroll
            for (int i = 0; i < 3; i++) {
                uint32_t w[4];
                ldsm4t(w, wa + s * SLOT + i * 2560);
                const uint4 a = hf[s * 3 + i];
                mma16816(acc[i * 2], a.x, a.x, a.y, a.y, w[0], w[1]);
                mma16816(acc[i * 2 + 1], a.z, a.z, a.w, a.w, w[2], w[3]);
            }
        }
        const float s0 = ((acc[0][0] + acc[1][0]) + (acc[2][0] + acc[3][0])) + (acc[4][0] + acc[5][0]);
        const float s1 = ((acc[0][1] + acc[1][1]) + (acc[2][1] + acc[3][1])) + (acc[4][1] + acc[5][1]);
        if (lane < 4) st_async2(raddr, s0, s1, rbar);
    } else if (warp < 4 && cr < 5) {
        const uint4* box = g_box + (size_t)oct * (NCTA * 2) + warp * 64 + lane;
        constexpr int BSTR = 32;
        uint4 v[2];
        uint32_t pend = 3u;
        if (lane < PSTART) mbar_wait(BAR(B_FULL + 24 + lane));
        __syncwarp();
        for (uint32_t n = 0; n < SPIN_LIMIT; n++) {
            ld_relaxed4_if(v[0], box, pend & 1u);
            ld_relaxed4_if(v[1], box + BSTR, pend & 2u);
            pend = (((v[0].x ^ tag) | (v[0].y ^ tag) | (v[0].z ^ tag) | (v[0].w ^ tag)) & 1u) |
                   (((v[1].x ^ tag) | (v[1].y ^ tag) | (v[1].z ^ tag) | (v[1].w ^ tag)) & 1u) * 2u;
            if (!__any_sync(0xffffffffu, pend)) break;
        }
        const float vx = __uint_as_float(v[0].x) + __uint_as_float(v[1].x), vy = __uint_as_float(v[0].y) + __uint_as_float(v[1].y);
        const float vz = __uint_as_float(v[0].z) + __uint_as_float(v[1].z), vw = __uint_as_float(v[0].w) + __uint_as_float(v[1].w);
        const bool b1 = lane & 2, b2 = lane & 4;
        float k0 = b1 ? vz : vx, k1 = b1 ? vw : vy;
        k0 += __shfl_xor_sync(0xffffffffu, b1 ? vx : vz, 2);
        k1 += __shfl_xor_sync(0xffffffffu, b1 ? vy : vw, 2);
        float s = b2 ? k1 : k0;
        s += __shfl_xor_sync(0xffffffffu, b2 ? k0 : k1, 4);
        s += __shfl_xor_sync(0xffffffffu, s, 8);
        s += __shfl_xor_sync(0xffffffffu, s, 16);
        if (lane < 8) {
            const int col = (lane & 1) * 4 + (lane & 2) + (lane >> 2);
            asm volatile("st.shared.f32 [%0], %1;" ::"r"(sbase + OFF_FIN + col * 16 + warp * 4), "f"(s) : "memory");
            mbar_arrive(BAR(B_W));
        }
    }
#undef BAR
}

typedef CUresult (*EncodeTiledFn)(CUtensorMap*, CUtensorMapDataType, cuuint32_t, void*, const cuuint64_t*, const cuuint64_t*,
                                  const cuuint32_t*, const cuuint32_t*, CUtensorMapInterleave, CUtensorMapSwizzle,
                                  CUtensorMapL2promotion, CUtensorMapFloatOOBfill);

void make_map(EncodeTiledFn fn, CUtensorMap* m, const void* ptr, uint64_t cols, uint64_t rows, uint32_t box_c, uint32_t box_r) {
    cuuint64_t dims[2] = {cols, rows};
    cuuint64_t strides[1] = {cols * 2};
    cuuint32_t box[2] = {box_c, box_r};
    cuuint32_t es[2] = {1, 1};
    fn(m, CU_TENSOR_MAP_DATA_TYPE_BFLOAT16, 2, const_cast<void*>(ptr), dims, strides, box, es, CU_TENSOR_MAP_INTERLEAVE_NONE,
       CU_TENSOR_MAP_SWIZZLE_NONE, CU_TENSOR_MAP_L2_PROMOTION_NONE, CU_TENSOR_MAP_FLOAT_OOB_FILL_NONE);
}

void make_map3(EncodeTiledFn fn, CUtensorMap* m, const void* ptr, uint64_t cols, uint64_t rows, uint32_t box_r, uint32_t box_b) {
    cuuint64_t dims[3] = {64, rows, cols / 64};
    cuuint64_t strides[2] = {cols * 2, 128};
    cuuint32_t box[3] = {64, box_r, box_b};
    cuuint32_t es[3] = {1, 1, 1};
    fn(m, CU_TENSOR_MAP_DATA_TYPE_BFLOAT16, 3, const_cast<void*>(ptr), dims, strides, box, es, CU_TENSOR_MAP_INTERLEAVE_NONE,
       CU_TENSOR_MAP_SWIZZLE_128B, CU_TENSOR_MAP_L2_PROMOTION_NONE, CU_TENSOR_MAP_FLOAT_OOB_FILL_NONE);
}

void make_map3r(EncodeTiledFn fn, CUtensorMap* m, const void* ptr, uint64_t cols, uint64_t rows, uint32_t box_b, uint32_t box_r) {
    cuuint64_t dims[3] = {64, cols / 64, rows};
    cuuint64_t strides[2] = {128, cols * 2};
    cuuint32_t box[3] = {64, box_b, box_r};
    cuuint32_t es[3] = {1, 1, 1};
    fn(m, CU_TENSOR_MAP_DATA_TYPE_BFLOAT16, 3, const_cast<void*>(ptr), dims, strides, box, es, CU_TENSOR_MAP_INTERLEAVE_NONE,
       CU_TENSOR_MAP_SWIZZLE_128B, CU_TENSOR_MAP_L2_PROMOTION_NONE, CU_TENSOR_MAP_FLOAT_OOB_FILL_NONE);
}

}

extern "C" void kernel_launch(void* const* d_in, const int* in_sizes, int n_in, void* d_out, int out_size) {
    (void)in_sizes; (void)n_in; (void)out_size;
    static EncodeTiledFn encode = nullptr;
    if (!encode) {
        cudaFuncSetAttribute(fused_decode_kernel, cudaFuncAttributeMaxDynamicSharedMemorySize, SMEM_BYTES);
        void* fn = nullptr;
        cudaDriverEntryPointQueryResult qr;
        cudaGetDriverEntryPoint("cuTensorMapEncodeTiled", &fn, cudaEnableDefault, &qr);
        encode = (EncodeTiledFn)fn;
    }
    Maps maps;
    make_map(encode, &maps.m[0], d_in[3], NHEAD * DHEAD, D_MODEL, DHEAD, 32);
    make_map(encode, &maps.m[1], d_in[6], DFF, D_MODEL, 96, 16);
    make_map(encode, &maps.m[2], d_in[7], DFF, D_MODEL, 96, 16);
    make_map3r(encode, &maps.m[3], d_in[2], DHEAD, (uint64_t)NHEAD * SK, 3, 32);
    make_map3(encode, &maps.m[4], d_in[4], D_MODEL, NHEAD * DHEAD, 48, 2);
    make_map(encode, &maps.m[5], d_in[8], D_MODEL, DFF, 40, 96);
    const __nv_bfloat16* x  = (const __nv_bfloat16*)d_in[0];
    const __nv_bfloat16* kc = (const __nv_bfloat16*)d_in[1];
    const __nv_bfloat16* gw = (const __nv_bfloat16*)d_in[9];
    fused_decode_kernel<<<NCTA, NTHREADS, SMEM_BYTES>>>(maps, x, kc, gw, (const __nv_bfloat16*)d_in[3],
                                                        (__nv_bfloat16*)d_out);
}
```
